```python
import torch

def _softmax(x, axis=-1):
    return torch.softmax(x, dim=axis)
def _gelu(x):
    return torch.nn.functional.gelu(x, approximate="tanh")
def _silu(x):
    return torch.nn.functional.silu(x)
def _sigmoid(x):
    return torch.sigmoid(x)
def _layernorm(x, axis=-1, eps=1e-5):
    m = x.mean(dim=axis, keepdim=True)
    v = x.var(dim=axis, keepdim=True, unbiased=False)
    return (x - m) / torch.sqrt(v + eps)
def _scatter_add(tgt, idx, src, axis=0):
    return tgt.clone().index_add_(axis, idx, src)
def _segment_sum(src, seg, n):
    out = torch.zeros((n,) + src.shape[1:], dtype=src.dtype)
    return out.index_add_(0, seg, src)
def _pad(x, pw):
    flat = tuple(v for pair in reversed(pw) for v in pair)
    return torch.nn.functional.pad(x, flat)

kernel_name = 'recurrent_scan__ssm_conv_s4__moe_arch_mod__prompt'

def setup_inputs():

    _w = (lambda a: (lambda t: t.to(torch.bfloat16) if t.is_floating_point() else t)(torch.as_tensor(a)))
    def _A_setup():
        B, L, D, N = 1, 2048, 576, 128
        A_re = -(lambda _x: torch.exp(torch.as_tensor(_x)))((lambda *s: torch.randn(*s, dtype=torch.bfloat16) * 6.4)(D, N))
        A_im = torch.pi * (lambda *s: torch.randn(*s, dtype=torch.bfloat16) * 0.05)(D, N)
        B_re = (lambda *s: torch.randn(*s, dtype=torch.bfloat16) * 0.1)(D, N)
        B_im = (lambda *s: torch.randn(*s, dtype=torch.bfloat16) * 0.1)(D, N)
        C_re = (lambda *s: torch.randn(*s, dtype=torch.bfloat16) * 0.1)(D, N)
        C_im = (lambda *s: torch.randn(*s, dtype=torch.bfloat16) * 0.1)(D, N)
        log_dt = (lambda *s: torch.randn(*s, dtype=torch.bfloat16) * 0.05)(D) * 0.5 - 4.0
        Dskip = (lambda *s: torch.randn(*s, dtype=torch.bfloat16) * 0.05)(D)
        return {
            "u": _w((lambda *s: torch.randn(*s, dtype=torch.bfloat16) * 0.05)(B, L, D)),
            "A_re": _w(A_re),
            "A_im": _w(A_im),
            "B_re": _w(B_re),
            "B_im": _w(B_im),
            "C_re": _w(C_re),
            "C_im": _w(C_im),
            "log_dt": _w(log_dt),
            "Dskip": _w(Dskip),
        }
    _A_in = _A_setup()

    def _B_setup():
        B, S, D, F, C = 1, 2048, 576, 4608, 8
        return {
            "x": _w((lambda *s: torch.randn(*s, dtype=torch.bfloat16) * 0.05)(B, S, D)),
            "w_r": _w((lambda *s: torch.randn(*s, dtype=torch.bfloat16) * 0.05)(D)),
            "w_gate": _w((lambda *s: torch.randn(*s, dtype=torch.bfloat16) * 0.05)(D, F)),
            "w_up": _w((lambda *s: torch.randn(*s, dtype=torch.bfloat16) * 0.05)(D, F)),
            "w_down": _w((lambda *s: torch.randn(*s, dtype=torch.bfloat16) * 0.05)(F, D)),
        }
    _B_in = _B_setup()

    return {
        "A_u": _A_in["u"],
        "A_A_re": _A_in["A_re"],
        "A_A_im": _A_in["A_im"],
        "A_B_re": _A_in["B_re"],
        "A_B_im": _A_in["B_im"],
        "A_C_re": _A_in["C_re"],
        "A_C_im": _A_in["C_im"],
        "A_log_dt": _A_in["log_dt"],
        "A_Dskip": _A_in["Dskip"],
        "B_x": _B_in["x"],
        "B_w_r": _B_in["w_r"],
        "B_w_gate": _B_in["w_gate"],
        "B_w_up": _B_in["w_up"],
        "B_w_down": _B_in["w_down"],
    }

def reference(A_u, A_A_re, A_A_im, A_B_re, A_B_im, A_C_re, A_C_im, A_log_dt, A_Dskip, B_x, B_w_r, B_w_gate, B_w_up, B_w_down):
    def _A_ref(u, A_re, A_im, B_re, B_im, C_re, C_im, log_dt, Dskip):
        Bsz, L, D = u.shape
        dt = torch.exp(log_dt)[:, None]
        A = A_re + 1j * A_im
        Bc = B_re + 1j * B_im
        Cc = C_re + 1j * C_im
        logdA = dt * A
        dB = dt * Bc
        l = (lambda x, dt: x.to(dt))(torch.arange(L), A_re.dtype)
        P = torch.exp(logdA[:, :, None] * l[None, None, :])
        K = torch.einsum("dn,dnl,dn->dl", Cc, P, dB).real
        L2 = 2 * L
        Kp = _pad(K, ((0, 0), (0, L)))
        up = (lambda x, *d: x.permute(*d))(u, 0, 2, 1)
        up = _pad(up, ((0, 0), (0, 0), (0, L)))
        Kf = (lambda x, axes=(-2,-1): torch.fft.rfft2(x.float(), dim=axes))(Kp[:, None, :], axes=(-2, -1))
        Uf = (lambda x, axes=(-2,-1): torch.fft.rfft2(x.float(), dim=axes))(up[:, :, None, :], axes=(-2, -1))
        Yf = Uf * Kf[None, :, :, :]
        y = (lambda x, s, axes=(-2,-1): torch.fft.irfft2(x, s=s, dim=axes).to(torch.bfloat16))(Yf, (1, L2), axes=(-2, -1))[:, :, 0, :L]
        y = (lambda x, *d: x.permute(*d))(y, 0, 2, 1) + u * Dskip[None, None, :]
        return y

    def _B_ref(x, w_r, w_gate, w_up, w_down):
        B, S, D = x.shape
        C = 8
        r = x @ w_r
        idx = torch.argsort(-r, axis=-1)[:, :C]
        idx_e = (lambda x, n, axis: torch.repeat_interleave(x, n, dim=axis))(idx.reshape(B, C, 1), D, axis=2)
        x_sel = (lambda x, i, axis: torch.take_along_dim(x, i, dim=axis))(x, idx_e, axis=1)
        g = _silu(x_sel @ w_gate)
        u = x_sel @ w_up
        y = (g * u) @ w_down
        r_sel = _sigmoid((lambda x, i, axis: torch.take_along_dim(x, i, dim=axis))(r, idx, axis=1))
        y = y * r_sel.reshape(B, C, 1)
        b_off = (torch.arange(B) * S).reshape(B, 1)
        flat_idx = (idx + b_off).reshape(B * C)
        zero = (x * 0.0).reshape(B * S, D)
        upd = _scatter_add(zero, flat_idx, y.reshape(B * C, D), axis=0)
        return x + upd.reshape(B, S, D)

    x = A_u
    xn = _layernorm(x, axis=-1)
    s = _A_ref(xn, A_A_re, A_A_im, A_B_re, A_B_im, A_C_re, A_C_im, A_log_dt, A_Dskip)
    g = _silu(_B_ref(xn, B_w_r, B_w_gate, B_w_up, B_w_down))
    return x + s * g
```

```cpp
#include <cuda_runtime.h>
#include <cuda_bf16.h>
#include <cuda_fp16.h>
#include <cuda.h>
#include <stdint.h>
#include <stddef.h>

#define SAFE_WAITS 0
#define KDEBUG 0

namespace {

constexpr int L_ = 2048, D_ = 576, F_ = 4608;
constexpr int NMAIN = 128, NDOWN = 108, NCTA = 132, NTHREADS = 608;
constexpr int SPIN_LIMIT = 1 << 15;

constexpr int SM_SKIP = 480, SM_TAG = 484;
constexpr int SM_STAT = 512;
constexpr int SM_GU = 1024, STAGE = 8192;
constexpr int SM_SLOT = 74752, SLOT = 24640;
constexpr int T_ADD = 2176, T_W4 = 2304, T_W8 = 2688, T_INV = 2976, T_PAD = 3056;
constexpr int T_X = 4416;
constexpr int T_B3 = 8768, T_B5 = 11856, T_B7 = 14944, T_B9 = 17024;
constexpr int T_F = 19104, T_S2 = 22368;
constexpr int SM_ROWS = 198016, ROW = 592;
constexpr int SM_XS = 216960, SM_PART = SM_XS;
constexpr int SM_WR = 227200, SM_DSK = 227776, SM_ONES = 228368, SM_TAB = 228944;
constexpr int SM_TOTAL = 232448;
constexpr int KG_SCR = 3072;
constexpr int SV_GU = 2048, SV_XS = 223232, SV_CAND = 512;
static_assert(SM_GU + 9 * STAGE == SM_SLOT && SM_SLOT + 5 * SLOT <= SM_ROWS && SM_ROWS + 32 * ROW == SM_XS && SM_ROWS % 128 == 0, "map");
static_assert(T_PAD + 5 * 272 == T_X && T_X + 16 * 272 == T_B3 && T_S2 + 8 * 272 <= SLOT && SLOT % 128 == 64, "map");

enum { B_ROWS = 0, B_ST, B_GO, B_X, B_K = 6, B_DONE = 11, B_FREE, B_SEL, B_F, B_W = 24, B_COUNT = 60 };
enum { N_KB = 1, N_X1 = 6, N_WG = 7 };

struct LaneTab { uint32_t w[5][32][4]; };
constexpr LaneTab make_tab() {
    LaneTab T{};
    for (int l = 0; l < 32; l++) {
        const int g = l >> 2, t = l & 3, mi = l >> 3, j = l & 7, h = mi & 1, hf = mi >> 1;
        auto xad = [](int c) { return T_X + 16 * (c + (c < 0 ? -1 : c >> 4)); };
        const int v[5][4] = {
            {T_X + 272 * j + 16 * (((mi + 1) >> 1) - 1), T_X + 272 * j + (mi ? 16 * (((mi + 1) >> 1) - 1) : -32), 4 * (7 + g - 2 * t), 4 * 36864 * g + 16 * t},
            {((j & 1) ? T_B5 : T_B3) + 16 * (7 + h - (j & 6) - hf), ((j & 1) ? T_B9 : T_B7 + 16) + 16 * (14 + h - (j & 6) - 8 * hf), T_F + 272 * hf + 32 * j + 16 * h, T_W4 + 8 * (g + t)},
            {(hf && j >= 4 ? T_F + 272 * (j - 4) : T_PAD) + 16 * h, (hf ? T_F + 272 * 4 : T_S2) + 272 * j + 16 * h, T_W8 + 4 * (g + t), 0},
            {xad(l - 2) + 8, xad(l - 1), xad(l), l == 0 ? T_B3 : l == 1 ? T_B5 : T_B9},
            {512 * mi + 16 * j, T_X + (j & 1) * SLOT + 272 * (j >> 1) + 16 * mi, 512 * g + 16 * t, T_X + 272 * j + 16 * mi}};
        for (int k = 0; k < 5; k++)
            for (int q = 0; q < 4; q++) T.w[k][l][q] = (uint32_t)v[k][q];
    }
    return T;
}
__device__ const __align__(128) LaneTab g_tab = make_tab();

struct Tune { int t_w, w1, t_w2, w2, ws1, ws2, d_x, d_x2, t_key, t_xs, t_x, n_go, n_w, g_late, seq, zero, swap; };

struct Scratch {
    uint4 x[288 * 512];
    uint4 y[64 * 576 * 4];
    uint4 xs[4][640];
    uint32_t h[144 * 128];
    float part[36 * 12 * 128];
    uint2 key[L_];
    uint32_t cnt[36][32];
};
__device__ __align__(1024) Scratch g_s;
constexpr uint32_t G_X = offsetof(Scratch, x), G_Y = offsetof(Scratch, y), G_XS = offsetof(Scratch, xs), G_H = offsetof(Scratch, h), G_PART = offsetof(Scratch, part),
                   G_KEY = offsetof(Scratch, key), G_CNT = offsetof(Scratch, cnt);
__device__ uint32_t g_epoch[32] = {1};

struct Hot {
    const __nv_bfloat16 *are, *aim, *bre, *bim, *cre, *cim, *logdt, *u;
    const LaneTab* tab;
    char* s;
    uint32_t* epoch;
    const __nv_bfloat16 *wr, *dskip;
    __nv_bfloat16* out;
    Tune tn;
};
struct Maps { CUtensorMap u, gu, wd; };
#define TS(i) do {} while (0)

__device__ __forceinline__ uint32_t smem_u32(const void* p) { return (uint32_t)__cvta_generic_to_shared(p); }
__device__ __forceinline__ void mbar_init(uint32_t b, int c) { asm volatile("mbarrier.init.shared::cta.b64 [%0], %1;" ::"r"(b), "r"(c) : "memory"); }
__device__ __forceinline__ void mbar_expect(uint32_t b, int bytes) { asm volatile("mbarrier.arrive.expect_tx.shared::cta.b64 _, [%0], %1;" ::"r"(b), "r"(bytes) : "memory"); }
__device__ __forceinline__ bool elect() { uint32_t d; asm volatile("{.reg .pred p; elect.sync _|p, 0xffffffff; selp.u32 %0,1,0,p;}" : "=r"(d)); return d; }
__device__ __forceinline__ void mbar_arrive(uint32_t b, uint32_t n) {
    asm volatile("{.reg .pred p; bar.warp.sync 0xffffffff; elect.sync _|p, 0xffffffff; @p mbarrier.arrive.shared::cta.b64 _, [%0], %1;}" ::"r"(b), "r"(n) : "memory");
}
__device__ __forceinline__ void mbar_arrive(uint32_t b) {
    asm volatile("{.reg .pred p; bar.warp.sync 0xffffffff; elect.sync _|p, 0xffffffff; @p mbarrier.arrive.shared::cta.b64 _, [%0];}" ::"r"(b) : "memory");
}
#define WAIT_LOOP(ins) "{\n.reg .pred p;\nLW:\n" ins " p, [%0], 0;\n@!p bra LW;\n}"
__device__ __forceinline__ void mbar_wait(uint32_t b) { asm volatile(WAIT_LOOP("mbarrier.try_wait.parity.shared::cta.b64")::"r"(b) : "memory"); }
__device__ __forceinline__ uint32_t mapa(uint32_t a, uint32_t rank) { uint32_t d; asm("mapa.shared::cluster.u32 %0, %1, %2;" : "=r"(d) : "r"(a), "r"(rank)); return d; }
__device__ __forceinline__ void tma3d(uint32_t dst, const CUtensorMap* m, int c0, int c1, uint32_t bar) {
    asm volatile("cp.async.bulk.tensor.3d.shared::cluster.global.mbarrier::complete_tx::bytes [%0], [%1, {%3, %4, %5}], [%2];" ::"r"(dst), "l"(m), "r"(bar), "r"(c0), "r"(c1), "r"(0) : "memory");
}
__device__ __forceinline__ void wgmma8(float (&d)[4], uint32_t alo, uint32_t ahi, uint32_t blo) {
    asm volatile("{.reg .b64 da, db; mov.b64 da, {%4, %5}; mov.b64 db, {%6, %7};\n"
                 "wgmma.mma_async.sync.aligned.m64n8k16.f32.bf16.bf16 {%0,%1,%2,%3}, da, db, 1, 1, 1, 1, 1;}"
                 : "+f"(d[0]), "+f"(d[1]), "+f"(d[2]), "+f"(d[3]) : "r"(alo), "r"(ahi), "r"(blo), "r"(8));
}
__device__ __forceinline__ void pf_tmap(const CUtensorMap* m) { asm volatile("prefetch.tensormap [%0];" ::"l"(m) : "memory"); }
__device__ __forceinline__ void bar_sync(int id, int n) { asm volatile("bar.sync %0, %1;" ::"r"(id), "r"(n) : "memory"); }
__device__ __forceinline__ void bar_arrive(int id, int n) { asm volatile("bar.arrive %0, %1;" ::"r"(id), "r"(n) : "memory"); }
__device__ __forceinline__ uint4 ld_rlx4(const void* p) { uint4 v; asm volatile("ld.relaxed.gpu.global.v4.u32 {%0,%1,%2,%3}, [%4];" : "=r"(v.x), "=r"(v.y), "=r"(v.z), "=r"(v.w) : "l"(p) : "memory"); return v; }
__device__ __forceinline__ uint32_t ld_rlx(const void* p) { uint32_t v; asm volatile("ld.relaxed.gpu.global.u32 %0, [%1];" : "=r"(v) : "l"(p) : "memory"); return v; }
__device__ __forceinline__ uint32_t ldg16(const void* p) { uint16_t v; asm volatile("ld.global.nc.u16 %0, [%1];" : "=h"(v) : "l"(p)); return v; }
__device__ __forceinline__ uint32_t ldg32(const void* p) { uint32_t v; asm volatile("ld.global.nc.u32 %0, [%1];" : "=r"(v) : "l"(p)); return v; }
__device__ __forceinline__ void bulk_g2s(uint32_t dst, const void* src, int bytes, uint32_t bar) {
    asm volatile("cp.async.bulk.shared::cluster.global.mbarrier::complete_tx::bytes [%0], [%1], %2, [%3];" ::"r"(dst), "l"(src), "r"(bytes), "r"(bar) : "memory");
}
__device__ __forceinline__ void stg128(void* p, uint32_t x, uint32_t y, uint32_t z, uint32_t w) { asm volatile("st.global.v4.u32 [%0], {%1,%2,%3,%4};" ::"l"(p), "r"(x), "r"(y), "r"(z), "r"(w) : "memory"); }
__device__ __forceinline__ void stg32(void* p, uint32_t v) { asm volatile("st.global.u32 [%0], %1;" ::"l"(p), "r"(v) : "memory"); }
__device__ __forceinline__ uint32_t lds32(uint32_t a) { uint32_t v; asm volatile("ld.shared.u32 %0, [%1];" : "=r"(v) : "r"(a) : "memory"); return v; }
__device__ __forceinline__ uint32_t lds16(uint32_t a) { uint16_t v; asm volatile("ld.shared.u16 %0, [%1];" : "=h"(v) : "r"(a) : "memory"); return v; }
__device__ __forceinline__ uint2 lds64(uint32_t a) { uint2 v; asm volatile("ld.shared.v2.u32 {%0,%1}, [%2];" : "=r"(v.x), "=r"(v.y) : "r"(a) : "memory"); return v; }
__device__ __forceinline__ uint4 lds128(uint32_t a) { uint4 v; asm volatile("ld.shared.v4.u32 {%0,%1,%2,%3}, [%4];" : "=r"(v.x), "=r"(v.y), "=r"(v.z), "=r"(v.w) : "r"(a) : "memory"); return v; }
__device__ __forceinline__ float4 lds128f(uint32_t a) { float4 v; asm volatile("ld.shared.v4.f32 {%0,%1,%2,%3}, [%4];" : "=f"(v.x), "=f"(v.y), "=f"(v.z), "=f"(v.w) : "r"(a) : "memory"); return v; }
__device__ __forceinline__ void sts32(uint32_t a, uint32_t v) { asm volatile("st.shared.u32 [%0], %1;" ::"r"(a), "r"(v) : "memory"); }
__device__ __forceinline__ void sts64(uint32_t a, uint32_t x, uint32_t y) { asm volatile("st.shared.v2.u32 [%0], {%1,%2};" ::"r"(a), "r"(x), "r"(y) : "memory"); }
__device__ __forceinline__ void sts128(uint32_t a, uint32_t x, uint32_t y, uint32_t z, uint32_t w) { asm volatile("st.shared.v4.u32 [%0], {%1,%2,%3,%4};" ::"r"(a), "r"(x), "r"(y), "r"(z), "r"(w) : "memory"); }
__device__ __forceinline__ void st_async(uint32_t a, float v, uint32_t bar) {
    asm volatile("st.async.shared::cluster.mbarrier::complete_tx::bytes.f32 [%0], %1, [%2];" ::"r"(a), "f"(v), "r"(bar) : "memory");
}
__device__ __forceinline__ void ldm4(uint32_t a, uint32_t (&r)[4]) {
    asm volatile("ldmatrix.sync.aligned.m8n8.x4.shared.b16 {%0,%1,%2,%3}, [%4];" : "=r"(r[0]), "=r"(r[1]), "=r"(r[2]), "=r"(r[3]) : "r"(a) : "memory");
}
__device__ __forceinline__ void ldm4t(uint32_t a, uint32_t (&r)[4]) {
    asm volatile("ldmatrix.sync.aligned.m8n8.x4.trans.shared.b16 {%0,%1,%2,%3}, [%4];" : "=r"(r[0]), "=r"(r[1]), "=r"(r[2]), "=r"(r[3]) : "r"(a) : "memory");
}
__device__ __forceinline__ void ldm2(uint32_t a, uint32_t& r0, uint32_t& r1) {
    asm volatile("ldmatrix.sync.aligned.m8n8.x2.shared.b16 {%0,%1}, [%2];" : "=r"(r0), "=r"(r1) : "r"(a) : "memory");
}
__device__ __forceinline__ void stm4(uint32_t a, uint32_t r0, uint32_t r1, uint32_t r2, uint32_t r3) {
    asm volatile("stmatrix.sync.aligned.m8n8.x4.shared.b16 [%0], {%1,%2,%3,%4};" ::"r"(a), "r"(r0), "r"(r1), "r"(r2), "r"(r3) : "memory");
}
__device__ __forceinline__ void stm4t(uint32_t a, uint32_t r0, uint32_t r1, uint32_t r2, uint32_t r3) {
    asm volatile("stmatrix.sync.aligned.m8n8.x4.trans.shared.b16 [%0], {%1,%2,%3,%4};" ::"r"(a), "r"(r0), "r"(r1), "r"(r2), "r"(r3) : "memory");
}
__device__ __forceinline__ void stm2t(uint32_t a, uint32_t r0, uint32_t r1) {
    asm volatile("stmatrix.sync.aligned.m8n8.x2.trans.shared.b16 [%0], {%1,%2};" ::"r"(a), "r"(r0), "r"(r1) : "memory");
}
__device__ __forceinline__ void mma_bf(float (&c)[4], const uint32_t (&a)[4], uint32_t b0, uint32_t b1) {
    asm volatile("mma.sync.aligned.m16n8k16.row.col.f32.bf16.bf16.f32 {%0,%1,%2,%3},{%4,%5,%6,%7},{%8,%9},{%0,%1,%2,%3};"
                 : "+f"(c[0]), "+f"(c[1]), "+f"(c[2]), "+f"(c[3]) : "r"(a[0]), "r"(a[1]), "r"(a[2]), "r"(a[3]), "r"(b0), "r"(b1));
}
__device__ __forceinline__ void mma_h(float (&c)[4], const uint32_t (&a)[4], uint32_t b0, uint32_t b1) {
    asm volatile("mma.sync.aligned.m16n8k16.row.col.f32.f16.f16.f32 {%0,%1,%2,%3},{%4,%5,%6,%7},{%8,%9},{%0,%1,%2,%3};"
                 : "+f"(c[0]), "+f"(c[1]), "+f"(c[2]), "+f"(c[3]) : "r"(a[0]), "r"(a[1]), "r"(a[2]), "r"(a[3]), "r"(b0), "r"(b1));
}
__device__ __forceinline__ void mma_hh(uint32_t (&d)[2], const uint32_t (&c)[2], const uint32_t (&a)[4], uint32_t b0, uint32_t b1) {
    asm volatile("mma.sync.aligned.m16n8k16.row.col.f16.f16.f16.f16 {%0,%1},{%2,%3,%4,%5},{%6,%7},{%8,%9};"
                 : "=r"(d[0]), "=r"(d[1]) : "r"(a[0]), "r"(a[1]), "r"(a[2]), "r"(a[3]), "r"(b0), "r"(b1), "r"(c[0]), "r"(c[1]));
}
__device__ __forceinline__ uint32_t pack_bf(float lo, float hi) { uint32_t r; asm("cvt.rn.bf16x2.f32 %0, %1, %2;" : "=r"(r) : "f"(hi), "f"(lo)); return r; }
__device__ __forceinline__ uint32_t pack_h(float lo, float hi) { uint32_t r; asm("cvt.rn.f16x2.f32 %0, %1, %2;" : "=r"(r) : "f"(hi), "f"(lo)); return r; }
__device__ __forceinline__ float bf_lo(uint32_t w) { return __uint_as_float(w << 16); }
__device__ __forceinline__ float bf_hi(uint32_t w) { return __uint_as_float(w & 0xFFFF0000u); }
__device__ __forceinline__ float bf_round(float x) { return __uint_as_float(pack_bf(0.f, x)); }
__device__ __forceinline__ uint32_t bmul(uint32_t a, uint32_t b) { uint32_t r; asm("mul.rn.bf16x2 %0, %1, %2;" : "=r"(r) : "r"(a), "r"(b)); return r; }
__device__ __forceinline__ uint32_t bfma(uint32_t a, uint32_t b, uint32_t c) { uint32_t r; asm("fma.rn.bf16x2 %0, %1, %2, %3;" : "=r"(r) : "r"(a), "r"(b), "r"(c)); return r; }
__device__ __forceinline__ uint32_t hadd(uint32_t a, uint32_t b) { uint32_t r; asm("add.rn.f16x2 %0, %1, %2;" : "=r"(r) : "r"(a), "r"(b)); return r; }
__device__ __forceinline__ uint32_t hmul(uint32_t a, uint32_t b) { uint32_t r; asm("mul.rn.f16x2 %0, %1, %2;" : "=r"(r) : "r"(a), "r"(b)); return r; }
__device__ __forceinline__ uint32_t hfma(uint32_t a, uint32_t b, uint32_t c) { uint32_t r; asm("fma.rn.f16x2 %0, %1, %2, %3;" : "=r"(r) : "r"(a), "r"(b), "r"(c)); return r; }
__device__ __forceinline__ uint32_t prmt(uint32_t a, uint32_t b, uint32_t s) { uint32_t r; asm("prmt.b32 %0, %1, %2, %3;" : "=r"(r) : "r"(a), "r"(b), "r"(s)); return r; }
__device__ __forceinline__ uint32_t settag(uint32_t v, uint32_t tag) { uint32_t r; asm("lop3.b32 %0, %1, %2, 1, 0xD8;" : "=r"(r) : "r"(v), "r"(tag)); return r; }
__device__ __forceinline__ float ex2f(float x) { float r; asm("ex2.approx.ftz.f32 %0, %1;" : "=f"(r) : "f"(x)); return r; }
__device__ __forceinline__ float rcpf(float x) { float r; asm("rcp.approx.ftz.f32 %0, %1;" : "=f"(r) : "f"(x)); return r; }
__device__ __forceinline__ float sqrt_ap(float x) { float r; asm("sqrt.approx.ftz.f32 %0, %1;" : "=f"(r) : "f"(x)); return r; }
__device__ __forceinline__ float silu_f(float x) { return x * rcpf(1.f + ex2f(-1.4426950408889634f * x)); }
__device__ __forceinline__ float silu_half(float h) { float r; asm("tanh.approx.f32 %0, %1;" : "=f"(r) : "f"(h)); return fmaf(h, r, h); }
__device__ __forceinline__ uint32_t clk32() { uint32_t c; asm volatile("mov.u32 %0, %%clock;" : "=r"(c)); return c; }
__device__ __forceinline__ void spin_until(uint32_t t) {
    asm volatile("{\n.reg .pred p;\n.reg .s32 c;\nLS:\nnanosleep.u32 20;\nmov.u32 c, %%clock;\nsub.s32 c, c, %0;\nsetp.lt.s32 p, c, 0;\n@p bra.uni LS;\n}" ::"r"(t) : "memory");
}
__device__ __forceinline__ void wait_flag(const void* p, uint32_t v) {
    int it = SPIN_LIMIT;
#pragma unroll 1
    while (__any_sync(~0u, ld_rlx(p) != v && --it >= 0)) {}
}
__device__ __forceinline__ uint32_t movm(uint32_t v) { uint32_t r; asm volatile("movmatrix.sync.aligned.m8n8.trans.b16 %0, %1;" : "=r"(r) : "r"(v)); return r; }
__device__ __forceinline__ void cp16(uint32_t dst, const void* src) { asm volatile("cp.async.cg.shared.global [%0], [%1], 16;" ::"r"(dst), "l"(src) : "memory"); }
__device__ __forceinline__ void fence_async() { asm volatile("fence.proxy.async.shared::cta;" ::: "memory"); }
__device__ __forceinline__ uint32_t stale(uint32_t bad, uint32_t v, uint32_t tag) { uint32_t r; asm("lop3.b32 %0, %1, %2, %3, 0xF6;" : "=r"(r) : "r"(bad), "r"(v), "r"(tag)); return r; }
template <int N, int STEP>
__device__ __forceinline__ void poll(uint4 (&v)[N], const char* src, uint32_t tag) {
    int it = SPIN_LIMIT;
    bool again;
#pragma unroll 1
    do {
        uint32_t bad = 0;
#pragma unroll
        for (int k = 0; k < N; k++) v[k] = ld_rlx4(src + k * STEP);
#pragma unroll
        for (int k = 0; k < N; k++) bad = stale(bad, v[k].x, tag);
        again = __any_sync(~0u, (bad & 1) && --it >= 0);
    } while (again);
}

struct cf { float x, y; };
__device__ __forceinline__ cf cmul(cf a, cf b) { return {a.x * b.x - a.y * b.y, a.x * b.y + a.y * b.x}; }
__device__ __forceinline__ cf csq(cf a) { return {a.x * a.x - a.y * a.y, (a.x + a.x) * a.y}; }
__device__ __forceinline__ cf cexp2(float zr2, float zi) {
    const float mag = ex2f(zr2);
    return {mag * __cosf(zi), mag * __sinf(zi)};
}
__device__ __forceinline__ __half2 as_h2(uint32_t v) { return *reinterpret_cast<__half2*>(&v); }
__device__ __forceinline__ uint32_t as_u32(__half2 v) { return *reinterpret_cast<uint32_t*>(&v); }
struct hm { uint32_t v, s; };
__device__ __forceinline__ hm mk_hm(cf a) { return {pack_h(a.x, a.y), pack_h(-a.y, a.x)}; }
__device__ __forceinline__ uint32_t operator*(uint32_t x, hm y) {
    const __half2 xx = as_h2(x);
    return as_u32(__hfma2(__high2half2(xx), as_h2(y.s), __hmul2(__low2half2(xx), as_h2(y.v))));
}
struct KParams { uint32_t are, aim, bre, bim, cre, cim, ldt; };

__device__ __forceinline__ void kgen(const KParams& kp, uint32_t scr, uint32_t l16) {
    const float dt = bf_round(ex2f(bf_lo(kp.ldt) * 1.4426950408889634f));
    cf w = cmul({bf_lo(kp.cre), bf_lo(kp.cim)}, {dt * bf_lo(kp.bre), dt * bf_lo(kp.bim)});
    const uint32_t eb = min(max(__reduce_max_sync(~0u, __float_as_uint(fmaxf(fabsf(w.x), fabsf(w.y)))) & 0x7F800000u, 0x00800000u), 0x7E000000u);
    const float sc = __uint_as_float(0x7F000000u - eb);
    w.x *= sc; w.y *= sc;
    const uint32_t k0 = pack_h(0.f, (float)__reduce_add_sync(~0u, __float2int_rn(w.x * 16777216.f)) * (1.f / 16777216.f));
    const float zr = dt * bf_lo(kp.are) * 1.4426950408889634f, zi = dt * bf_lo(kp.aim);
    const uint32_t st0 = l16 ^ ((l16 >> 3) & 48), st1 = st0 ^ 64, lb = (st0 & 112) + 8 * (l16 & 112), la = 8 * (l16 & 240) + ((l16 ^ (l16 >> 4)) & 112);
    auto st = [&](int row, uint32_t a, uint32_t b, uint32_t c, uint32_t e) { stm4(((row & 4) ? st1 : st0) + scr + row * 128, a, b, c, e); };
    uint32_t a[4][4], d[5][2];
    {
        const cf a16 = cexp2(16.f * zr, -16.f * zi), a32 = csq(a16), a64 = csq(a32);
        const hm m32 = mk_hm(a32), m64 = mk_hm(a64), m128 = mk_hm(csq(a64));
        const uint32_t p1 = pack_h(a16.x, a16.y), p2 = m32.v, p3 = p1 * m32, p5 = p1 * m64, p6 = p2 * m64, p7 = p3 * m64;
        st(0, 0x00003C00u, p1, p2, p3);
        st(4, m64.v, p5, p6, p7);
        st(8, m128.v, p1 * m128, p2 * m128, p3 * m128);
        st(12, m64.v * m128, p5 * m128, p6 * m128, p7 * m128);
        __syncwarp();
#pragma unroll
        for (int k = 0; k < 4; k++) ldm4((la ^ (k * 32)) + scr, a[k]);
    }
    auto tile = [&](int T, int row) {
        d[T][0] = d[T][1] = 0u;
#pragma unroll
        for (int k = 0; k < 2; k++) {
            uint32_t b[4];
            ldm4((lb ^ (k * 64)) + scr + row * 128, b);
            mma_hh(d[T], d[T], a[2 * k], b[0], b[1]);
            mma_hh(d[T], d[T], a[2 * k + 1], b[2], b[3]);
        }
    };
    const cf a1 = cexp2(zr, zi), a2 = csq(a1), a4 = csq(a2), u1 = cmul(w, a1);
    const hm m1 = mk_hm(a1), m2 = mk_hm(a2), m4 = mk_hm(a4), m8 = mk_hm(csq(a4));
    uint32_t v[17], e[9];
    v[1] = pack_h(u1.x, u1.y);
    v[2] = v[1] * m1;
    v[3] = v[1] * m2; v[4] = v[2] * m2;
#pragma unroll
    for (int i = 1; i <= 4; i++) v[4 + i] = v[i] * m4;
#pragma unroll
    for (int i = 1; i <= 8; i++) v[8 + i] = v[i] * m8;
    const cf a256 = cexp2(256.f * zr, 256.f * zi), a512 = csq(a256);
    const hm m256 = mk_hm(a256), m512 = mk_hm(a512), m1024 = mk_hm(csq(a512));
#pragma unroll
    for (int i = 1; i <= 8; i++) e[i] = v[2 * i] * m256;
    __syncwarp();
    st(0, v[1], v[2], v[5], v[6]);
    st(4, v[9], v[10], v[13], v[14]);
    st(8, v[3], v[4], v[7], v[8]);
    st(12, v[11], v[12], v[15], v[16]);
    st(16, e[1], e[2], e[3], e[4]);
    st(20, e[5], e[6], e[7], e[8]);
    __syncwarp();
    tile(0, 0); tile(1, 8); tile(2, 16);
    const uint32_t f8 = v[8] * m512, f16 = v[16] * m512, g8 = e[4] * m512, g16 = e[8] * m512;
    __syncwarp();
    st(0, v[4] * m512, f8, v[12] * m512, f16);
    st(4, e[2] * m512, g8, e[6] * m512, g16);
    st(8, v[8] * m1024, v[16] * m1024, e[4] * m1024, e[8] * m1024);
    st(12, f8 * m1024, f16 * m1024, g8 * m1024, g16 * m1024);
    __syncwarp();
    tile(3, 0); tile(4, 8);
    __syncwarp();
    sts128(scr + l16, d[2][0], d[2][1], k0, eb);
    sts128(scr + l16 + 512, d[0][0], d[1][0], d[0][1], d[1][1]);
    sts128(scr + l16 + 1024, d[3][0], d[3][1], d[4][0], d[4][1]);
}

__device__ __forceinline__ void ktables(uint32_t tab, int far, int lane) {
    uint4 c[4], v[4];
#pragma unroll
    for (int q = 0; q < 4; q++) { c[q] = lds128(tab + T_B3 + q * KG_SCR + lane * 16); v[q] = lds128(tab + T_B3 + q * KG_SCR + lane * 16 + 512 + 512 * far); }
    const uint32_t eb = max(max(c[0].w, c[1].w), max(c[2].w, c[3].w));
    const float rs = __uint_as_float(0x7F000000u - eb);
    uint32_t s[7] = {0u, 0u, 0u, 0u, 0u, 0u, 0u};
#pragma unroll
    for (int q = 0; q < 4; q++) {
        const float ff = __uint_as_float(c[q].w) * rs;
        const uint32_t f = pack_h(ff, ff);
        s[0] = hfma(v[q].x, f, s[0]); s[1] = hfma(v[q].y, f, s[1]); s[2] = hfma(v[q].z, f, s[2]); s[3] = hfma(v[q].w, f, s[3]);
        s[4] = hfma(c[q].x, f, s[4]); s[5] = hfma(c[q].y, f, s[5]); s[6] = hfma(c[q].z, f, s[6]);
    }
    if (far) {
        const int g = lane >> 2, t = lane & 3;
        const uint32_t a4 = tab + T_W4 + 4 * (14 + 2 * g + 32 * (t >> 1) + (t & 1)), a8 = tab + T_W8 + 4 * (7 + g + 16 * t);
        sts32(a4, hmul(s[0], 0x20002000u)); sts32(a4 + 64, hmul(s[1], 0x20002000u));
        sts32(a8, hmul(s[2], 0x20002000u)); sts32(a8 + 32, hmul(s[3], 0x20002000u));
        if (lane == 31) {
            sts32(tab + T_ADD + 28, 0x5800u); sts32(tab + T_ADD + 32, 0x58000000u);
            sts32(tab + T_ADD + 60, s[1] >> 16); sts32(tab + T_ADD + 64, s[1] & 0xFFFF0000u);
            sts32(tab + T_INV, prmt(eb + 0x00800000u, 0u, 0x3232));
        }
    } else {
        const uint32_t o = tab + 32 + lane * 16;
        const bool last = lane == 31;
        const uint32_t q0 = __shfl_sync(~0u, last ? s[6] : s[1], lane - 1), q1 = __shfl_sync(~0u, last ? s[1] : s[3], lane - 1);
        const uint32_t q2 = __shfl_sync(~0u, last ? s[3] : s[4], lane - 1), q3 = __shfl_sync(~0u, last ? s[4] : s[5], lane - 1);
        sts128(o, prmt(s[0], q0, 0x7610), prmt(s[0], 0u, 0x1032), prmt(s[1], s[0], 0x7610), prmt(s[1], 0u, 0x1032));
        sts128(o + 512, prmt(s[2], q1, 0x7610), prmt(s[2], 0u, 0x1032), prmt(s[3], s[2], 0x7610), prmt(s[3], 0u, 0x1032));
        sts128(o + 1024, prmt(q2, 0u, 0x3232), prmt(s[4], q2, 0x7610), prmt(s[4], 0u, 0x1032), prmt(s[4], 0u, 0x3232));
        const uint32_t aa = prmt(s[5], 0u, 0x3232);
        sts128(o + 1536, prmt(q3, 0u, 0x3232), prmt(s[5], q3, 0x7610), prmt(s[5], 0u, 0x1032), aa);
        if (last) { sts128(o + 1552, aa, aa, s[5] & 0xFFFF0000u, 0u); sts32(tab + 28, s[6] >> 16); }
    }
}

__device__ __forceinline__ void boxes(uint32_t slot, uint32_t r0, int n, uint4 lt, uint32_t l16) {
    uint32_t xi = slot + 544 * r0, o = slot + 512 * r0 + l16;
    sts128(lt.w + slot, 0u, 0u, 0u, 0u);
#pragma unroll 1
    do {
        const uint2 pv = lds64(lt.x + xi);
        const uint4 ow = lds128(lt.y + xi), nx = lds128(lt.z + xi);
        const uint32_t P[9] = {pv.x, pv.y, ow.x, ow.y, ow.z, ow.w, nx.x, nx.y, nx.z};
        uint32_t Q[8], S2[8], S4[6], b5[5];
#pragma unroll
        for (int k = 0; k < 8; k++) { Q[k] = prmt(P[k], P[k + 1], 0x5432); S2[k] = hadd(P[k], Q[k]); }
#pragma unroll
        for (int k = 0; k < 6; k++) S4[k] = hadd(S2[k], S2[k + 1]);
#pragma unroll
        for (int k = 0; k < 5; k++) b5[k] = hadd(S4[k + 1], P[k + 3]);
        const uint32_t b30 = hadd(Q[3], S2[4]);
        sts128(o + T_B3 + 16, b30, hadd(Q[4], S2[5]), hadd(Q[5], S2[6]), hadd(Q[6], S2[7]));
        sts128(o + T_B5 + 16, b5[0], b5[1], b5[2], b5[3]);
        if (n > 1) {
            sts128(o + T_B7 + 16, hadd(hadd(Q[0], S2[1]), S4[2]), hadd(hadd(Q[1], S2[2]), S4[3]), hadd(hadd(Q[2], S2[3]), S4[4]), hadd(b30, S4[5]));
            sts128(o + T_B9 + 16, hadd(S4[0], b5[1]), hadd(S4[1], b5[2]), hadd(S4[2], b5[3]), hadd(S4[3], b5[4]));
            sts128(lt.z + xi + (T_S2 - T_X), S2[4], S2[5], S2[6], S2[7]);
        }
        xi += 1088; o += 1024;
        asm volatile("" : "+r"(n));
    } while (--n);
}

#define CT(i)
__device__ __forceinline__ void conv_far(uint32_t slot, int nb, uint32_t fbar, bool all, uint32_t tb) {
    const uint4 lb = lds128(tb + 512);
    const uint32_t wa = lds32(tb + 1032) + slot;
    uint2 w4[10];
    uint32_t w8[8][2], f[12][2];
#pragma unroll
    for (int s = 0; s < 10; s++) w4[s] = lds64(lb.w + slot + 32 * s);
#pragma unroll
    for (int k = 0; k < 12; k++) f[k][0] = f[k][1] = 0u;
    auto it = [&](int i) {
        uint32_t q[3][4];
        ldm4t(lb.x + slot + 256 * i, q[0]);
        if (i >= 4) ldm4t(lb.y + slot + 256 * (i - 4), q[2]);
        ldm4t(lb.x + slot + 256 * i + 128, q[1]);
#pragma unroll
        for (int k = i; k < min(i + 5, 12); k++) mma_hh(f[k], f[k], q[0], w4[1 + 2 * (k - i)].x, w4[1 + 2 * (k - i)].y);
        if (i >= 4) {
#pragma unroll
            for (int k = i; k < 12; k++) mma_hh(f[k], f[k], q[2], w8[k - i][0], w8[k - i][1]);
        }
#pragma unroll
        for (int k = i; k < min(i + 5, 12); k++) mma_hh(f[k], f[k], q[1], w4[2 * (k - i)].x, w4[2 * (k - i)].y);
        if (i & 1) stm4t(lb.z + slot + 272 * (i - 1), f[i - 1][0], f[i - 1][1], f[i][0], f[i][1]);
    };
    bar_sync(nb, 64);
    CT(0);
#pragma unroll
    for (int i = 0; i < 4; i++) it(i);
#pragma unroll
    for (int s = 0; s < 8; s++) { w8[s][0] = lds32(wa + 32 * s); w8[s][1] = lds32(wa + 32 * s + 16); }
    mbar_arrive(fbar);
    CT(1);
    if (all) {
#pragma unroll
        for (int i = 4; i < 12; i++) it(i);
        mbar_arrive(fbar + 8);
    }
    CT(2);
}

__device__ __forceinline__ void conv_near(uint32_t slot, uint32_t fbar, int H, char* gs, uint32_t yoff, uint32_t ci, uint32_t tb, uint32_t tag, uint32_t z, uint32_t nb, int nseq) {
    float acc[8][4];
    const uint4 la = lds128(tb);
    uint32_t xa = la.x + slot + 2176 * H, xb = la.y + slot + 2176 * H, ra = la.z + slot;
    uint32_t q[8][4], r[2][2];
    r[0][0] = lds32(ra + 32); r[0][1] = lds32(ra);
#pragma unroll
    for (int i = 7; i >= 0; i--) ldm4((i ? xa : xb) + 32 * i, q[i]);
    auto step = [&](int s) {
        r[~s & 1][0] = lds32(ra + 64 * s + 96); r[~s & 1][1] = lds32(ra + 64 * s + 64);
        mma_h(acc[7], q[(7 - s) & 7], r[s & 1][0], r[s & 1][1]);
        q[(7 - s) & 7][3] = q[(8 - s) & 7][0] | z;
        ldm2(s == 7 ? xb - 272 : xa - 48 - 32 * s - (s & 8) * 2, q[(7 - s) & 7][0], q[(7 - s) & 7][1]);
#pragma unroll
        for (int i = 6; i >= 0; i--) mma_h(acc[i], q[(i - s) & 7], r[s & 1][0], r[s & 1][1]);
        q[(7 - s) & 7][2] = q[(7 - s) & 7][1] | z;
    };
#pragma unroll
    for (int i = 0; i < 8; i++) acc[i][0] = acc[i][1] = acc[i][2] = acc[i][3] = 0.f;
    step(0);
    CT(0);
#pragma unroll 1
    for (int n = 0; n < 4; n++) {
#pragma unroll
        for (int s = 1; s <= 8; s++) step(s);
        xa -= 272; xb -= 272; ra += 512;
        if (n == nseq) bar_arrive(nb, 64);
    }
    CT(1);
    uint32_t aa = lds32(tb + 1024 + 4 * H) + slot, b0 = lds32(ra + T_ADD - 2048 + 32), b1 = lds32(ra + T_ADD - 2048), inv = lds32(slot + T_INV);
    char* yo = gs + (la.w + yoff);
    mbar_wait(fbar + 8 * H);
    CT(2);
    asm volatile("{.reg .pred p; elect.sync _|p, 0xffffffff; @p red.relaxed.gpu.global.add.u32 [%0], 1;}" ::"l"(gs + G_CNT + ci) : "memory");
#pragma unroll
    for (int a = 0; a < 4; a++) {
#pragma unroll
        for (int i = 2 * a; i < 2 * a + 2; i++) {
            ldm4(aa + 32 * i, q[i]);
            mma_h(acc[i], q[i], b0, b1);
        }
        stg128(yo + G_Y + a * 36864, settag(bmul(pack_bf(acc[2 * a][0], acc[2 * a][1]), inv), tag), bmul(pack_bf(acc[2 * a][2], acc[2 * a][3]), inv),
               bmul(pack_bf(acc[2 * a + 1][0], acc[2 * a + 1][1]), inv), bmul(pack_bf(acc[2 * a + 1][2], acc[2 * a + 1][3]), inv));
    }
    CT(3);
}

__global__ void __cluster_dims__(2, 1, 1) __launch_bounds__(NTHREADS, 1) fused_kernel(const Hot p, const __grid_constant__ Maps m) {
    extern __shared__ __align__(1024) char smem[];
    const uint32_t t0 = clk32();
    const uint32_t tid = threadIdx.x, lane = tid & 31, bid = blockIdx.x, r = bid & 1, rb = bid >> 1;
    uint32_t c5 = 288 * (bid >> 6) + 256 + (rb & 31), c0 = c5 + (rb & 31) - 192 - 64 * r;
    uint32_t S = smem_u32(smem), l16 = 16 * lane;
    asm volatile("" : "+r"(S), "+r"(l16), "+r"(c0), "+r"(c5));
    const uint32_t warp = __shfl_sync(~0u, tid >> 5, 0), sub = warp & 3, grp = warp >> 2;
    uint32_t tag;
    const uint32_t ns = (bid * 171) >> 11, kq = bid - 12 * ns;
    uint32_t w0 = SM_GU, xs = SM_XS, bar = S + B_W * 8, slice = bid;

    if (bid < NMAIN) {
        if (warp == 16) {
            if (elect()) {
                mbar_init(S + B_ROWS * 8, 1);
                asm volatile("mbarrier.expect_tx.relaxed.cta.shared::cta.b64 [%0], %1;" ::"r"(S + B_ROWS * 8), "n"(32 * ROW + 1152) : "memory");
                tma3d(S + SM_ROWS, &m.u, 144 * r, 32 * rb, S + B_ROWS * 8);
                bulk_g2s(S + SM_WR, p.wr + 288 * r, 576, S + B_ROWS * 8);
                bulk_g2s(S + SM_DSK, p.dskip + 288 * r, 576, S + B_ROWS * 8);
                mbar_init(S + B_GO * 8, 8); mbar_init(S + B_ST * 8, 8);
#pragma unroll
                for (int i = B_X; i <= B_FREE; i++) mbar_init(S + i * 8, 4);
                asm volatile("mbarrier.expect_tx.relaxed.cta.shared::cta.b64 [%0], 2560;" ::"r"(S + B_GO * 8) : "memory");
                asm volatile("mbarrier.expect_tx.relaxed.cta.shared::cta.b64 [%0], 1024;" ::"r"(S + B_ST * 8) : "memory");
                asm volatile("mbarrier.expect_tx.relaxed.cta.shared::cta.b64 [%0], 3072;" ::"r"(S + (B_K + 4) * 8) : "memory");
                asm volatile("fence.mbarrier_init.release.cluster;" ::: "memory");
                pf_tmap(&m.gu); pf_tmap(&m.wd);
            }
            __syncthreads();
            asm volatile("barrier.cluster.arrive.relaxed.aligned;" ::: "memory");
            tag = ld_rlx(p.epoch);
            sts32(S + SM_TAG, tag);
            if (r) *(uint2*)(p.s + G_KEY + (256 * rb + 8 * lane)) = make_uint2(~tag, 0u);
            mbar_arrive(S + B_ROWS * 8);
            TS(0);
            spin_until(t0 + p.tn.t_w);
            if (elect()) {
                const CUtensorMap* mp = &m.gu;
                int col = 16 * bid, row = 0;
                uint32_t dst = S + SM_GU;
                bulk_g2s(S + SM_TAB, p.tab, 2560, S + B_GO * 8);
#pragma unroll 1
                for (int s = 0; s < 15; s++) {
                    const int w = s < p.tn.n_w ? p.tn.w1 : p.tn.w2;
                    if (s >= w) mbar_wait(bar - w * 8);
                    if (s == 9) {
                        if (bid >= NDOWN) break;
                        TS(2);
                        mbar_wait(S + B_FREE * 8);
                        col = 32 * ns; row = 384 * kq; mp = &m.wd; dst = S + SM_GU;
                    }
                    mbar_expect(bar, STAGE);
                    tma3d(dst, mp, col, row, bar);
                    dst += STAGE; row += 64; bar += 8;
                }
            }
            TS(1);
            goto out;
        }

        const uint32_t gq = grp >> 2, bi = sub - gq, ck = bi + (r & gq) * 2;
        KParams kp;
        {
            const uint32_t ko = (gq ? c5 : c0 + 64 * (grp & 2) + (grp & 1)) * 128 + 32 * ck + lane;
            kp.are = ldg16(p.are + ko); kp.aim = ldg16(p.aim + ko); kp.bre = ldg16(p.bre + ko);
            kp.bim = ldg16(p.bim + ko); kp.cre = ldg16(p.cre + ko); kp.cim = ldg16(p.cim + ko);
            kp.ldt = ldg16(p.logdt + (ko >> 7));
        }
        {
            {
                if (grp & 2) {
                    if (elect()) {
#pragma unroll
                        for (int i = 0; i < 4; i++) mbar_init(S + B_SEL * 8 + 32 * (warp - 8) + 8 * i, 1);
                    }
#pragma unroll 1
                    for (uint32_t i = 16 * tid - 4096; i < T_X; i += 4096)
#pragma unroll
                        for (int k = 0; k < 5; k++) sts128(S + SM_SLOT + k * SLOT + i, 0u, 0u, 0u, 0u);
                    if (tid >= 476) sts128(S + SM_ONES + 16 * (tid - 476), 0x3F803F80u, 0x3F803F80u, 0x3F803F80u, 0x3F803F80u);
                }
                __syncthreads();
                asm volatile("barrier.cluster.arrive.relaxed.aligned;" ::: "memory");
                if (grp == 4 && p.tn.g_late) mbar_wait(S + B_GO * 8);
                if (grp & 2) {
                    const uint32_t kh = grp & 1, t = lane & 3;
                    uint32_t ad = S + ((lane & 8) ? ((lane & 7) ? SM_WR : SM_ONES) : SM_ROWS + ROW * (8 * sub + (lane & 7))) + 288 * kh + (lane & 16);
                    uint32_t pa = S + SM_PART + 1024 * r + 128 * (warp - 8) + 4 * (lane & 28), xa = S + SM_ROWS + 37 * l16 + 16 * (warp - 8);
                    char* dst = p.s + G_X + ((144 * r + 4 * (warp - 8) + (lane >> 3)) * 8192 + 128 * rb + (l16 & 112));
                    float d[3][4];
#pragma unroll
                    for (int i = 0; i < 3; i++) d[i][0] = d[i][1] = d[i][2] = d[i][3] = 0.f;
                    asm volatile("barrier.cluster.wait.aligned;" : "+r"(ad), "+r"(pa), "+r"(xa), "+l"(dst)::"memory");
                    mbar_wait(S + B_ROWS * 8);
                    TS(0);
#pragma unroll
                    for (int k = 0; k < 9; k++) {
                        uint32_t a[4];
                        ldm4(ad + 32 * k, a);
                        mma_bf(d[k % 3], a, a[0], a[2]);
                    }
#pragma unroll
                    for (int i = 0; i < 4; i++) d[0][i] += d[1][i] + d[2][i];
                    const float s0 = __shfl_sync(~0u, d[0][2], t), s1 = __shfl_sync(~0u, d[0][3], t), w1 = __shfl_sync(~0u, d[0][2], t + 4);
                    const bool odd = lane & 4;
                    const float q = odd ? d[0][1] : d[0][0], s = odd ? s1 : s0, w = odd ? d[0][3] : w1;
                    asm volatile("{.reg .pred p; setp.eq.u32 p, %0, %1;\n"
                                 "@p st.async.shared::cluster.mbarrier::complete_tx::bytes.v4.f32 [%2], {%5,%6,%7,%7}, [%3];\n"
                                 "@p st.shared.v4.f32 [%4], {%5,%6,%7,%7};}"
                                 ::"r"(lane >> 3), "r"(t), "r"(pa ^ (1u << 24)), "r"((S ^ (1u << 24)) + B_ST * 8), "r"(pa), "f"(q), "f"(s), "f"(w) : "memory");
                    mbar_arrive(S + B_ST * 8);
                    const uint32_t tg = lds32(S + SM_TAG + (l16 >> 9));
                    mbar_wait(S + B_ST * 8);
                    TS(1);
                    float4 v[4];
#pragma unroll
                    for (int i = 0; i < 4; i++) v[i] = lds128f(S + SM_PART + 512 * i + l16);
                    const float mean = ((v[0].y + v[1].y) + (v[2].y + v[3].y)) * (1.f / 576.f);
                    const float var = fmaxf(((v[0].x + v[1].x) + (v[2].x + v[3].x)) * (1.f / 576.f) - mean * mean, 0.f);
                    const uint32_t ms = pack_bf(mean, sqrt_ap(bf_round(bf_round(var) + 1e-5f)));
                    const float ri = 0.5f * rcpf(bf_hi(ms));
                    sts64(S + SM_STAT + 8 * lane, __float_as_uint(ri), __float_as_uint(-bf_lo(ms) * ri));
                    if (warp + 8 * r == 15 + 8) *(uint2*)(p.s + G_KEY + (256 * rb + 8 * lane)) = make_uint2(settag(__float_as_uint((v[0].z + v[1].z) + (v[2].z + v[3].z)), tg), ms);
                    __syncwarp();
#pragma unroll
                    for (int i = 0; i < 4; i++) v[i] = lds128f(S + SM_STAT + 64 * i + (l16 & 48));
#pragma unroll 1
                    for (int b = kh; b < 5; b++) {
                        uint32_t x[4];
                        ldm4t(xa, x);
#pragma unroll
                        for (int i = 0; i < 4; i++) x[i] = pack_h(fmaf(bf_lo(x[i]), v[i].x, v[i].y), fmaf(bf_hi(x[i]), v[i].z, v[i].w));
                        stg128(dst, settag(x[0], tg), x[1], x[2], x[3]);
                        xa += 128; dst += 32 * 8192;
                        if (b == p.tn.n_go) mbar_arrive(S + B_GO * 8);
                    }
                    TS(2);
                }
            }
            const uint32_t scr = S + SM_SLOT + T_B3 + grp * SLOT + ck * KG_SCR;
            kgen(kp, scr, l16);
            TS(4);
            if (gq) {
                fence_async();
                asm volatile("barrier.cluster.wait.aligned;" ::: "memory");
                if (elect())
                    asm volatile("cp.async.bulk.shared::cluster.shared::cta.mbarrier::complete_tx::bytes [%0], [%1], 1536, [%2];"
                                 ::"r"(scr ^ (1u << 24)), "r"(scr), "r"((S ^ (1u << 24)) + (B_K + 4) * 8) : "memory");
            }
            mbar_arrive(S + (B_K + grp) * 8, 1 + gq);
        }
        {
            const uint32_t ts = gq ? 4 : sub;
            {
#pragma unroll 1
                for (uint32_t ph = (ts | grp) & 2;; ph += 2) {
                    if (ph == 2) {
                        mbar_wait(S + B_GO * 8);
                        tag = lds32(S + SM_TAG + (l16 >> 9));
                        if (grp & 2) break;
                        const uint2 lr = lds64(S + SM_TAB + 2048 + l16 + 8 * gq);
                        const uint32_t ww = gq ? 2 * bi : 2 * grp + (sub & 1);
                        const char* src = p.s + G_X + (lr.x + 2048 * ww + (gq ? (c5 >> 1) * 8192 + 64 * (c5 & 1) : (c0 + 64 * (sub & 2)) * 4096));
                        const uint32_t xd = lr.y + S + SM_SLOT + SLOT * (ts & 6) + 1088 * ww;
                        spin_until(t0 + max(clk32() - t0, p.tn.t_x) + (ts >= 2 ? p.tn.d_x2 : p.tn.d_x));
                        uint4 v[4];
                        poll<4, 128>(v, src, tag);
#pragma unroll
                        for (int k = 0; k < 4; k++) stm4(xd + k * 64, v[k].x, v[k].y, v[k].z, v[k].w);
                        TS(6);
                    } else {
                        mbar_wait(S + (B_K + ts) * 8);
                        ktables(S + SM_SLOT + ts * SLOT, gq ? bi : grp, lane);
                        TS(5);
                    }
                    if (ph != (ts & 2)) {
                        mbar_arrive(S + B_X * 8 + 4 * (ts & 6), 1 + gq);
                        break;
                    }
                }
            }
        }
        if (grp != 3) {
            {
                const uint32_t sl = warp == 8 ? 4 : grp == 4 ? 4 * bi : sub, slot = S + SM_SLOT + sl * SLOT, fb = S + B_F * 8 + 16 * sl, tb = S + SM_TAB + l16;
                const bool far = warp > 8, all = sl + r < 5;
                const uint4 lt = lds128(tb + 1536);
                mbar_wait(S + B_X * 8 + 4 * (sl & 6));
                TS(9);
                if (grp) boxes(slot, far, all ? 3 : 1, lt, l16);
                TS(8);
                if (far) {
                    conv_far(slot, 1 + sl, fb, all, tb);
                    TS(7);
                } else {
                    if (grp) bar_arrive(1 + sl, 64);
                    if (warp - 5 < 3) bar_sync(11 + sub, 64);
                    const uint32_t ch = sl == 4 ? c5 : c0 + 64 * (sl & 2) + (sl & 1), H = grp && all;
                    conv_near(slot, fb, H, p.s, 32 * 36864 * H + 64 * ch, 8 * (ch & ~31u) + 128 * H, tb, tag, p.tn.zero, 11 + sub, warp - 1 < 3 ? p.tn.seq : -1);
                    if (grp == rb >> 5) mbar_arrive(S + B_DONE * 8);
                    TS(7);
                    if (grp) goto out;
                }
            }
            const uint32_t oc = 64 * (warp - 5 * (grp >> 1)), g = lane >> 2, lc = oc + (l16 & 48);
            uint32_t cc[4][4], gt[4][4], xa = S + SM_ROWS + ROW * g + lc, sa = S + SM_STAT + 8 * g;
            uint4 dk = lds128(S + SM_DSK + lc);
            dk.x = bmul(dk.x, 0x40004000u); dk.y = bmul(dk.y, 0x40004000u); dk.z = bmul(dk.z, 0x40004000u); dk.w = bmul(dk.w, 0x40004000u);
#pragma unroll 1
            for (int i = 0; i < 4; i++) {
                const uint4 x4 = lds128(xa);
                const uint2 st = lds64(sa);
                const uint32_t x[4] = {x4.x, x4.y, x4.z, x4.w}, d[4] = {dk.x, dk.y, dk.z, dk.w};
#pragma unroll
                for (int b = 0; b < 4; b++) {
                    const float h0 = fmaf(bf_lo(x[b]), __uint_as_float(st.x), __uint_as_float(st.y)), h1 = fmaf(bf_hi(x[b]), __uint_as_float(st.x), __uint_as_float(st.y));
#pragma unroll
                    for (int q = 0; q < 3; q++) { cc[q][b] = cc[q + 1][b]; gt[q][b] = gt[q + 1][b]; }
                    gt[3][b] = pack_bf(silu_half(h0), silu_half(h1));
                    cc[3][b] = bfma(bmul(pack_bf(h0, h1), d[b]), gt[3][b], x[b]);
                }
                xa += 8 * ROW; sa += 64;
            }
            char* oa = (char*)p.out + ((32 * rb + g) * 1152 + 576 * r + lc);
            const char* ya = p.s + G_Y + (bid * 18432 + 32 * oc + 4 * (l16 & 384) + (l16 & 112));
            mbar_wait(S + B_SEL * 8);
            const uint32_t skip = lds32(S + SM_SKIP) >> g;
            mbar_wait(S + B_DONE * 8);
            TS(10);
            wait_flag(p.s + G_CNT + (2304 * r + 4 * oc + 128 * (rb >> 5) + (l16 >> 9)), 32 * tag);
            TS(11);
            uint4 y[4];
            poll<4, 128>(y, ya, tag);
            TS(12);
#pragma unroll
            for (int i = 0; i < 4; i++) {
                uint32_t o[4];
#pragma unroll
                for (int b = 0; b < 4; b++) o[b] = bfma(movm(i == 0 ? y[b].x : i == 1 ? y[b].y : i == 2 ? y[b].z : y[b].w), gt[i][b], cc[i][b]);
                if (!((skip >> (8 * i)) & 1)) stg128(oa + 9216 * i, o[0], o[1], o[2], o[3]);
            }
            TS(13);
            goto out;
        }
        if (bid < NDOWN) stg128(p.s + G_PART + (((4 * ns + sub) * 12 + kq) * 512 + l16), ~tag, ~tag, ~tag, ~tag);
        spin_until(t0 + p.tn.t_xs);
    } else {
        tag = ld_rlx(p.epoch + (lane & p.tn.zero));
        if (elect()) {
#pragma unroll
            for (int i = 0; i < 3; i++) mbar_init(S + B_W * 8 + 24 * min(warp, 11) + 8 * i, 1);
            if (warp == 16) { mbar_init(S + B_FREE * 8, 4); pf_tmap(&m.gu); }
        }
        __syncthreads();
        if (warp >= 16) {
            if (warp == 16 && elect()) {
                int done = 0, col = 64 * bid - 6144, row = 0;
                uint32_t dst = S + SV_GU;
                spin_until(t0 + p.tn.t_w);
#pragma unroll 1
                for (int s = 0; s < 36; s++) {
#pragma unroll 1
                    for (; s - done >= ((int)(clk32() - t0) < p.tn.t_w2 ? p.tn.ws1 : p.tn.ws2); done++) mbar_wait(S + (B_W + done) * 8);
                    if (s == 27) { mbar_wait(S + B_FREE * 8); fence_async(); dst = S + SV_GU; }
                    mbar_expect(S + (B_W + s) * 8, STAGE);
                    tma3d(dst, &m.gu, col, row, S + (B_W + s) * 8);
                    dst += STAGE; row += 64;
                    if (row == 576) { row = 0; col += 16; }
                }
            }
            TS(1);
            goto out;
        }
        const int t = lane & 3;
        uint4* xo = (uint4*)(p.s + G_XS) + 640 * (bid & 3) + 2 * tid;
        if (tid < 320) { stg128(xo, ~tag, 0u, 0u, 0u); stg128(xo + 1, ~tag, 0u, 0u, 0u); }
        if (tid == 0) sts32(S + SV_CAND, 0u);
        float sw = 0.f;
#pragma unroll
        for (int i = 0; i < 9; i++) { const uint32_t w = __ldg((const uint32_t*)p.wr + 32 * i + lane); sw += bf_lo(w) + bf_hi(w); }
#pragma unroll
        for (int o = 16; o > 0; o >>= 1) sw += __shfl_xor_sync(~0u, sw, o);
        spin_until(t0 + p.tn.t_key);
        uint4 v[2];
#pragma unroll 1
        for (int it = 0; it < SPIN_LIMIT; it++) {
            v[0] = ld_rlx4((const uint4*)(p.s + G_KEY) + tid); v[1] = ld_rlx4((const uint4*)(p.s + G_KEY) + tid + 512);
            if (!__any_sync(~0u, ((v[0].x ^ tag) | (v[0].z ^ tag) | (v[1].x ^ tag) | (v[1].z ^ tag)) & 1)) break;
        }
        TS(2);
        auto mk = [&](uint32_t dot, uint32_t ms, int row) {
            const uint32_t s = pack_bf(0.f, (__uint_as_float(dot) - bf_lo(ms) * sw) * rcpf(bf_hi(ms)));
            return ((s ^ (((int)s >> 31) | 0x80000000u)) & 0xFFFF0000u) | (uint32_t)(4095 - row);
        };
        const uint32_t k[4] = {mk(v[0].x, v[0].y, 2 * tid), mk(v[0].z, v[0].w, 2 * tid + 1), mk(v[1].x, v[1].y, 2 * tid + 1024), mk(v[1].z, v[1].w, 2 * tid + 1025)};
        const uint32_t km[4] = {v[0].y, v[0].w, v[1].y, v[1].w};
        const uint32_t kx = max(max(k[0], k[1]), max(k[2], k[3]));
        sts32(S + SV_CAND + 64 + 4 * warp, __reduce_max_sync(~0u, kx));
        bar_sync(N_X1, 512);
        TS(5);
        const uint32_t mine = lds32(S + SV_CAND + 64 + 4 * (lane & 15));
        const uint4 o0 = lds128(S + SV_CAND + 64 + 2 * (lane & 16)), o1 = lds128(S + SV_CAND + 80 + 2 * (lane & 16));
        int rank = (((o0.x > mine) + (o0.y > mine)) + ((o0.z > mine) + (o0.w > mine))) + (((o1.x > mine) + (o1.y > mine)) + ((o1.z > mine) + (o1.w > mine)));
        rank += __shfl_xor_sync(~0u, rank, 16);
        const uint32_t bound = __reduce_max_sync(~0u, rank == 7 ? mine : 0u);
        if (kx >= bound) {
            const int c = ((k[0] >= bound) + (k[1] >= bound)) + ((k[2] >= bound) + (k[3] >= bound));
            uint32_t pos;
            asm volatile("atom.shared.add.u32 %0, [%1], %2;" : "=r"(pos) : "r"(S + SV_CAND), "r"(8 * c) : "memory");
#pragma unroll
            for (int q = 0; q < 4; q++)
                if (k[q] >= bound) { sts64(S + SV_XS + pos, k[q], km[q]); pos += 8; }
        }
        bar_sync(N_X1, 512);
        TS(6);
        const int n8 = lds32(S + SV_CAND);
#pragma unroll 1
        for (int i = 8 * warp; i < n8; i += 128) {
            const uint2 c = lds64(S + SV_XS + i);
            rank = 0;
#pragma unroll 1
            for (int q = 8 * lane; q < n8; q += 256) rank += lds32(S + SV_XS + q) > c.x;
            rank = __reduce_add_sync(~0u, rank);
            const float ri = rcpf(bf_hi(c.y));
            if (rank < 8) sts128(S + SV_CAND + 128 + 16 * rank, c.x, c.y, c.y << 16, __float_as_uint(ri));
        }
        bar_sync(N_X1, 512);
        TS(3);
        if (tid < 288) {
            uint4 b[8];
            uint32_t x[8];
#pragma unroll
            for (int q = 0; q < 8; q++) { b[q] = lds128(S + SV_CAND + 128 + 16 * q); x[q] = ldg32((const uint32_t*)p.u + (4095 - (b[q].x & 4095)) * 288 + tid); }
            float lo[8], hi[8];
#pragma unroll
            for (int q = 0; q < 8; q++) {
                lo[q] = bf_round(bf_lo(x[q]) - __uint_as_float(b[q].z)) * __uint_as_float(b[q].w);
                hi[q] = bf_round(bf_hi(x[q]) - __uint_as_float(b[q].z)) * __uint_as_float(b[q].w);
            }
#pragma unroll
            for (int q = 0; q < 4; q++) { x[q] = pack_bf(lo[2 * q], lo[2 * q + 1]); x[4 + q] = pack_bf(hi[2 * q], hi[2 * q + 1]); }
            stg128(xo, settag(x[0], tag), x[1], x[2], x[3]);
            stg128(xo + 1, settag(x[4], tag), x[5], x[6], x[7]);
            sts128(S + SV_XS + 32 * tid, x[0], x[1], x[2], x[3]);
            sts128(S + SV_XS + 32 * tid + 16, x[4], x[5], x[6], x[7]);
            fence_async();
        } else if (tid < 320) {
#pragma unroll
            for (int q = 0; q < 2; q++) {
                const uint2 c = lds64(S + SV_CAND + 128 + 32 * t + 16 * q);
                const uint32_t k32 = c.x & 0xFFFF0000u, sb = (k32 ^ ((~(int)k32 >> 31) | 0x80000000u)) & 0xFFFF0000u;
                stg128(xo + q, settag(pack_bf(0.f, rcpf(1.f + ex2f(-1.4426950408889634f * __uint_as_float(sb)))) | ((4095 - (c.x & 4095)) << 1), tag), c.y, 0u, 0u);
            }
        }
        TS(4);
        bar_sync(N_X1, 512);
        w0 = SV_GU + (grp % 3) * 9 * STAGE; xs = SV_XS; bar = S + (B_W + 9 * grp) * 8; slice = 4 * bid + grp - 384;
    }

    {
    const uint32_t fi = tid & 127;
    char* ho = p.s + G_H + (512 * slice + 4 * lane);
    stg32(ho + 128 * sub, ~tag);
    float d[4];
#pragma unroll 1
    for (uint32_t ph = 0;; ph = 1) {
        if (bid < NMAIN) {
            const char* src = p.s + ((ph ? G_H + 6144 * kq : G_XS + 10240 * (bid & 3)) + 16 * fi);
            uint4 v[5];
            int it = SPIN_LIMIT;
            bool again;
            v[3].x = v[4].x = tag;
#pragma unroll 1
            do {
                uint32_t bad = 0;
#pragma unroll
                for (int k = 0; k < 5; k++)
                    if (k < 3 || !ph) v[k] = ld_rlx4(src + 2048 * k);
#pragma unroll
                for (int k = 0; k < 5; k++) bad = stale(bad, v[k].x, tag);
                again = __any_sync(~0u, (bad & 1) && --it >= 0);
            } while (again);
#pragma unroll
            for (int k = 0; k < 5; k++)
                if (k < 3 || !ph) sts128(S + SM_XS + 16 * fi + 2048 * k, v[k].x, v[k].y, v[k].z, v[k].w);
            fence_async();
            if (sub - ph == 3) {
                uint32_t bit;
                asm("shl.b32 %0, 1, %1;" : "=r"(bit) : "r"(((v[4].x >> 1) & 2047) - 32 * rb));
                sts32(S + SM_SKIP, __reduce_or_sync(~0u, bit));
                mbar_arrive(S + B_SEL * 8);
            }
            bar_sync(N_WG + 3, 128);
        }
        uint32_t alo = (((S & 0xFFFF) + w0) >> 4) + (256 << 16), blo = (((S & 0xFFFF) + xs) >> 4) + (8 << 16);
        const uint32_t ahi = ph ? 0x40000040u : 0x80000020u, ak = 64 << ph;
        d[0] = d[1] = d[2] = d[3] = 0.f;
#pragma unroll 1
        for (uint32_t s = 9 * ph; s < 9 + 6 * ph; s++) {
            mbar_wait(bar);
            asm volatile("wgmma.fence.sync.aligned;" ::: "memory");
#pragma unroll
            for (int k = 0; k < 4; k++) wgmma8(d, alo + k * ak, ahi, blo + 16 * k);
            asm volatile("wgmma.commit_group.sync.aligned;\nwgmma.wait_group.sync.aligned 1;" ::: "memory");
            alo += STAGE / 16; blo += 64; bar += 8;
            if (s == 6 && bid < NMAIN) mbar_arrive(S + B_FREE * 8);
        }
        asm volatile("wgmma.wait_group.sync.aligned 0;" : "+f"(d[0]), "+f"(d[1]), "+f"(d[2]), "+f"(d[3])::"memory");
        if (ph) break;
        TS(10);
        const uint32_t ex = S + w0 + 6 * STAGE + 8 * (fi & 63), v0 = pack_bf(d[0], d[1]), v1 = pack_bf(d[2], d[3]);
        const bool gate = (sub >> 1) == p.tn.swap;
        if (!gate) sts64(ex, v0, v1);
        bar_sync(N_WG + grp, 128);
        if (gate) {
            const uint2 u = lds64(ex);
            const uint32_t h0 = bmul(pack_bf(silu_half(0.5f * bf_lo(v0)), silu_half(0.5f * bf_hi(v0))), u.x);
            const uint32_t h1 = bmul(pack_bf(silu_half(0.5f * bf_lo(v1)), silu_half(0.5f * bf_hi(v1))), u.y);
            ho += 256 * (sub & 1);
            stg32(ho, settag(h0, (lane & 3) ? h0 : tag)); stg32(ho + 128, settag(h1, (lane & 3) ? h1 : tag));
        }
        if (!grp) mbar_arrive(S + B_FREE * 8);
        TS(11);
        if (bid >= NDOWN) goto out;
    }
    char* po = p.s + G_PART + (((4 * ns + sub) * 12 + kq) * 512 + 128 * (lane & 3) + (lane & 28));
#pragma unroll
    for (int i = 0; i < 4; i++) stg32(po + 64 * (i & 1) + 32 * (i >> 1), settag(__float_as_uint(d[i]), tag));
    TS(13);
    if (r && kq < 8) {
        const uint32_t tile = 4 * ns + (kq >> 1), cc = 16 * tile + (tid & 15);
        const uint2 rec = lds64(S + SM_XS + 9216 + (fi & 112));
        const uint32_t row = (rec.x >> 1) & 2047, oi = row * D_ + cc, xr = ldg16(p.u + oi), dk = ldg16(p.dskip + cc);
        const char* ya = p.s + G_Y + ((row >> 5) * 36864 + 64 * cc + 8 * (row & 6));
        const char* pa = p.s + G_PART + (tile * 6144 + 4 * fi);
        const char* fl = p.s + G_CNT + (128 * (tile & ~1u) + 128 * (row >> 10));
        uint32_t w[12], f = ld_rlx(fl);
        uint4 y;
        y.x = ~tag;
        int it = SPIN_LIMIT;
        bool again;
#pragma unroll 1
        do {
            if (f == 32 * tag) y = ld_rlx4(ya);
            f = ld_rlx(fl);
#pragma unroll
            for (int k = 0; k < 12; k++) w[k] = ld_rlx(pa + 512 * k);
            uint32_t bad = y.x ^ tag;
#pragma unroll
            for (int k = 0; k < 12; k++) bad = stale(bad, w[k], tag);
            again = __any_sync(~0u, (bad & 1) && --it >= 0);
        } while (again);
        float s3[3];
#pragma unroll
        for (int k = 0; k < 3; k++) s3[k] = (__uint_as_float(w[4 * k]) + __uint_as_float(w[4 * k + 1])) + (__uint_as_float(w[4 * k + 2]) + __uint_as_float(w[4 * k + 3]));
        const float x = bf_lo(xr), xn = bf_round(bf_round(x - bf_lo(rec.y)) * rcpf(bf_hi(rec.y)));
        const uint32_t yw = (row & 16) ? ((row & 8) ? y.w : y.z) : ((row & 8) ? y.y : y.x);
        const float sg = fmaf(xn, bf_lo(dk), (row & 1) ? bf_hi(yw) : bf_lo(yw));
        const float up = bf_round(bf_round(s3[0] + s3[1] + s3[2]) * bf_hi(rec.x));
        p.out[oi] = __float2bfloat16(fmaf(sg, silu_f(bf_round(xn + up)), x));
        if (bid + fi == 1) stg32(p.epoch, tag + 1);
        TS(14);
    }
    }
out:;
}

typedef CUresult (*EncodeFn)(CUtensorMap*, CUtensorMapDataType, cuuint32_t, void*, const cuuint64_t*, const cuuint64_t*, const cuuint32_t*,
                             const cuuint32_t*, CUtensorMapInterleave, CUtensorMapSwizzle, CUtensorMapL2promotion, CUtensorMapFloatOOBfill);

void make_map(EncodeFn enc, CUtensorMap* m, const void* base, uint64_t cols, uint64_t rows, uint64_t second, uint32_t bc, uint32_t br, CUtensorMapSwizzle sw) {
    cuuint64_t gd[3] = {cols / 2, rows, second ? 2u : 1u};
    cuuint64_t gs[2] = {cols * 2, second ? second : cols * 2 * rows};
    cuuint32_t bd[3] = {bc / 2, br, second ? 2u : 1u}, es[3] = {1, 1, 1};
    enc(m, CU_TENSOR_MAP_DATA_TYPE_UINT32, 3, const_cast<void*>(base), gd, gs, bd, es, CU_TENSOR_MAP_INTERLEAVE_NONE, sw,
        CU_TENSOR_MAP_L2_PROMOTION_L2_128B, CU_TENSOR_MAP_FLOAT_OOB_FILL_NONE);
}

Tune g_tune = {2000, 1, 7000, 2, 8, 16, 600, 900, 4500, 8600, 4300, 2, 2, 1, 0, 0, 0};

}

extern "C" void kernel_launch(void* const* d_in, const int* in_sizes, int n_in, void* d_out, int out_size) {
    static EncodeFn enc = nullptr;
    static char* gs = nullptr;
    static LaneTab* gt = nullptr;
    static uint32_t* ge = nullptr;
    if (!enc) {
        void* fn = nullptr;
        cudaDriverEntryPointQueryResult qr;
        cudaGetDriverEntryPoint("cuTensorMapEncodeTiled", &fn, cudaEnableDefault, &qr);
        enc = (EncodeFn)fn;
        cudaFuncSetAttribute(fused_kernel, cudaFuncAttributeMaxDynamicSharedMemorySize, SM_TOTAL);
        cudaGetSymbolAddress((void**)&gs, g_s);
        cudaGetSymbolAddress((void**)&ge, g_epoch);
        cudaGetSymbolAddress((void**)&gt, g_tab);
    }
    Hot p;
    Maps m;
    auto in = [&](int i) { return (const __nv_bfloat16*)d_in[i]; };
    p.u = in(0); p.are = in(1); p.aim = in(2); p.bre = in(3); p.bim = in(4); p.cre = in(5); p.cim = in(6);
    p.logdt = in(7); p.dskip = in(8); p.wr = in(10);
    p.out = (__nv_bfloat16*)d_out;
    p.tn = g_tune;
    p.s = gs;
    p.epoch = ge;
    p.tab = gt;
    const char *wg = (const char*)d_in[11], *wu = (const char*)d_in[12];
    p.tn.swap = wu < wg;
    make_map(enc, &m.u, in(0), D_, L_, 0, ROW / 2, 32, CU_TENSOR_MAP_SWIZZLE_NONE);
    make_map(enc, &m.gu, wu < wg ? wu : wg, F_, D_, wu < wg ? wg - wu : wu - wg, 32, 64, CU_TENSOR_MAP_SWIZZLE_64B);
    make_map(enc, &m.wd, in(13), D_, F_, 0, 64, 64, CU_TENSOR_MAP_SWIZZLE_128B);
    fused_kernel<<<NCTA, NTHREADS, SM_TOTAL>>>(p, m);
}
```

```cpp
#include <cuda_runtime.h>
#include <cuda_bf16.h>
#include <cuda_fp16.h>
#include <cuda.h>
#include <stdint.h>
#include <stddef.h>
#include <type_traits>

#define SAFE_WAITS 0
#define X_PRE 1
constexpr int PRE_UNROLL = X_PRE;
#define KDEBUG 0

namespace {

constexpr int L_ = 2048, D_ = 576, F_ = 4608;
constexpr int NMAIN = 128, NDOWN = 108, NCTA = 132, NTHREADS = 640;
constexpr int SPIN_LIMIT = 1 << 15;

constexpr int SM_SKIP = 448, SM_TAG = 452, SM_REC = 768;
constexpr int SM_STAT = 512;
constexpr int SM_GU = 1024, STAGE = 8192;
constexpr int SM_SLOT = 74752, SLOT = 24640;
constexpr int T_ADD = 2176, T_W4 = 2304, T_W8 = 2688, T_INV = 2976, T_PAD = 3056;
constexpr int T_X = 4416;
constexpr int T_B3 = 8768, T_B5 = 11856, T_B7 = 14944, T_B9 = 17024;
constexpr int T_F = 19104, T_S2 = 22368;
constexpr int SM_ROWS = 198016, ROW = 592;
constexpr int SM_XS = 216960, SM_PART = SM_XS;
constexpr int SM_WR = SM_XS + 2048, SM_ONES = SM_WR + 592, SM_DSK = 227328, SM_TAB = 227904;
constexpr int SM_TOTAL = 232448;
constexpr int KG_SCR = 3072;
constexpr int SV_CAND = 512, SV_XS = 896, SV_GU = 11264;
static_assert(SM_GU + 9 * STAGE == SM_SLOT && SM_SLOT + 5 * SLOT <= SM_ROWS && SM_ROWS + 32 * ROW == SM_XS && SM_ROWS % 128 == 0, "map");
static_assert(T_PAD + 5 * 272 == T_X && T_X + 16 * 272 == T_B3 && T_S2 + 8 * 272 <= SLOT && SLOT % 128 == 64, "map");

enum { B_X = 0, B_K = 2, B_T = 7, B_DONE = 12, B_FREE = 15, B_SEL, B_F = 18, B_W = 28, B_ROWS = 48, B_ST, B_GO };
enum { N_KB = 1, N_X1 = 6, N_WG = 7 };

struct LaneTab { uint32_t w[6][32][4]; };
constexpr LaneTab make_tab() {
    LaneTab T{};
    for (int l = 0; l < 32; l++) {
        const int g = l >> 2, t = l & 3, mi = l >> 3, j = l & 7, h = mi & 1, hf = mi >> 1;
        auto xad = [](int c) { return T_X + 16 * (c + (c < 0 ? -1 : c >> 4)); };
        const int v[6][4] = {
            {T_X + 272 * j + 16 * (((mi + 1) >> 1) - 1), T_X + 272 * j + (mi ? 16 * (((mi + 1) >> 1) - 1) : -32), 4 * (7 + g - 2 * t), 4 * 36864 * g + 16 * t},
            {((j & 1) ? T_B5 : T_B3) + 16 * (7 + h - (j & 6) - hf), ((j & 1) ? T_B9 : T_B7 + 16) + 16 * (14 + h - (j & 6) - 8 * hf), T_F + 272 * hf + 32 * j + 16 * h, T_W4 + 8 * (g + t)},
            {(hf && j >= 4 ? T_F + 272 * (j - 4) : T_PAD) + 16 * h, (hf ? T_F + 272 * 4 : T_S2) + 272 * j + 16 * h, T_W8 + 4 * (g + t), g == 2 * t ? 0x5800 : g == 2 * t + 1 ? 0x58000000 : 0},
            {xad(l - 2) + 8, xad(l - 1), xad(l), l == 0 ? T_B3 : l == 1 ? T_B5 : T_B9},
            {512 * mi + 16 * j, T_X + (j & 1) * SLOT + 272 * (j >> 1) + 16 * mi, 512 * g + 16 * t, T_X + 272 * j + 16 * mi},
            {SM_ROWS + ROW * g + 16 * t, SM_STAT + 8 * g, 1152 * g + 16 * t, g}};
        for (int k = 0; k < 6; k++)
            for (int q = 0; q < 4; q++) T.w[k][l][q] = (uint32_t)v[k][q];
    }
    return T;
}
__device__ const __align__(128) LaneTab g_tab = make_tab();

struct Tune { int t_w, w1, n_w, w2, ws1, n_sv, ws2, t_x, d_x, d_x2, t_key, t_xs, nap, late; };
#define TUNE 2000, 1, 4, 3, 12, 13, 16, 5300, 500, 800, 4500, 7000, 100, 1
constexpr Tune c_tune = {TUNE};
#define TN(x) std::integral_constant<int, c_tune.x>::value

struct Scratch {
    uint4 x[288 * 512];
    uint4 y[64 * 576 * 4];
    uint4 xs[16][8];
    uint32_t h[144 * 128];
    float part[44 * 12 * 128];
    uint2 key[L_];
    uint32_t cnt[36][32];
};
__device__ __align__(1024) Scratch g_s;
constexpr uint32_t G_X = offsetof(Scratch, x), G_Y = offsetof(Scratch, y), G_XS = offsetof(Scratch, xs), G_H = offsetof(Scratch, h), G_PART = offsetof(Scratch, part),
                   G_KEY = offsetof(Scratch, key), G_CNT = offsetof(Scratch, cnt);
__device__ uint32_t g_epoch[32] = {1};

struct Hot {
    const __nv_bfloat16 *are, *aim, *bre, *bim, *cre, *cim, *logdt, *u;
    const LaneTab* tab;
    char* s;
    uint32_t* epoch;
    const __nv_bfloat16 *wr, *dskip;
    __nv_bfloat16* out;
    uint32_t zero, swap;
};
struct alignas(128) Maps { CUtensorMap u, gu, wd; };
#define TS(i) do {} while (0)

__device__ __forceinline__ uint32_t smem_u32(const void* p) { return (uint32_t)__cvta_generic_to_shared(p); }
__device__ __forceinline__ void mbar_init(uint32_t b, int c) { asm volatile("mbarrier.init.shared::cta.b64 [%0], %1;" ::"r"(b), "r"(c) : "memory"); }
__device__ __forceinline__ void mbar_expect(uint32_t b, int bytes) { asm volatile("mbarrier.arrive.expect_tx.shared::cta.b64 _, [%0], %1;" ::"r"(b), "r"(bytes) : "memory"); }
__device__ __forceinline__ bool elect() { uint32_t d; asm volatile("{.reg .pred p; elect.sync _|p, 0xffffffff; selp.u32 %0,1,0,p;}" : "=r"(d)); return d; }
__device__ __forceinline__ void mbar_arrive(uint32_t b, uint32_t n) {
    asm volatile("{.reg .pred p; bar.warp.sync 0xffffffff; elect.sync _|p, 0xffffffff; @p mbarrier.arrive.shared::cta.b64 _, [%0], %1;}" ::"r"(b), "r"(n) : "memory");
}
__device__ __forceinline__ void mbar_arrive(uint32_t b) {
    asm volatile("{.reg .pred p; bar.warp.sync 0xffffffff; elect.sync _|p, 0xffffffff; @p mbarrier.arrive.shared::cta.b64 _, [%0];}" ::"r"(b) : "memory");
}
#define WAIT_LOOP(ins) "{\n.reg .pred p;\nLW:\n" ins " p, [%0], 0;\n@!p bra LW;\n}"
__device__ __forceinline__ void mbar_wait(uint32_t b) { asm volatile(WAIT_LOOP("bar.warp.sync 0xffffffff;\nmbarrier.try_wait.parity.shared::cta.b64")::"r"(b) : "memory"); }
__device__ __forceinline__ uint32_t mapa(uint32_t a, uint32_t rank) { uint32_t d; asm("mapa.shared::cluster.u32 %0, %1, %2;" : "=r"(d) : "r"(a), "r"(rank)); return d; }
__device__ __forceinline__ void tma3d(uint32_t dst, const CUtensorMap* m, int c0, int c1, uint32_t bar) {
    asm volatile("cp.async.bulk.tensor.3d.shared::cluster.global.mbarrier::complete_tx::bytes [%0], [%1, {%3, %4, %5}], [%2];" ::"r"(dst), "l"(m), "r"(bar), "r"(c0), "r"(c1), "r"(0) : "memory");
}
__device__ __forceinline__ void wgmma8(float (&d)[4], uint64_t da, uint64_t db) {
    asm volatile("wgmma.mma_async.sync.aligned.m64n8k16.f32.bf16.bf16 {%0,%1,%2,%3}, %4, %5, 1, 1, 1, 1, 0;"
                 : "+f"(d[0]), "+f"(d[1]), "+f"(d[2]), "+f"(d[3]) : "l"(da), "l"(db));
}
__device__ __forceinline__ void pf_tmap(const CUtensorMap* m) { asm volatile("prefetch.tensormap [%0];" ::"l"(m) : "memory"); }
__device__ __forceinline__ void bar_sync(int id, int n) { asm volatile("bar.sync %0, %1;" ::"r"(id), "r"(n) : "memory"); }
__device__ __forceinline__ void bar_arrive(int id, int n) { asm volatile("bar.arrive %0, %1;" ::"r"(id), "r"(n) : "memory"); }
__device__ __forceinline__ uint4 ld_rlx4(const void* p) { uint4 v; asm volatile("ld.relaxed.gpu.global.v4.u32 {%0,%1,%2,%3}, [%4];" : "=r"(v.x), "=r"(v.y), "=r"(v.z), "=r"(v.w) : "l"(p) : "memory"); return v; }
__device__ __forceinline__ uint32_t ld_rlx(const void* p) { uint32_t v; asm volatile("ld.relaxed.gpu.global.u32 %0, [%1];" : "=r"(v) : "l"(p) : "memory"); return v; }
__device__ __forceinline__ uint32_t ldg16(const void* p) { uint16_t v; asm volatile("ld.global.nc.u16 %0, [%1];" : "=h"(v) : "l"(p)); return v; }
__device__ __forceinline__ uint32_t ldg32(const void* p) { uint32_t v; asm volatile("ld.global.nc.u32 %0, [%1];" : "=r"(v) : "l"(p)); return v; }
__device__ __forceinline__ void bulk_g2s(uint32_t dst, const void* src, int bytes, uint32_t bar) {
    asm volatile("cp.async.bulk.shared::cluster.global.mbarrier::complete_tx::bytes [%0], [%1], %2, [%3];" ::"r"(dst), "l"(src), "r"(bytes), "r"(bar) : "memory");
}
__device__ __forceinline__ void stg128(void* p, uint32_t x, uint32_t y, uint32_t z, uint32_t w) { asm volatile("st.global.v4.u32 [%0], {%1,%2,%3,%4};" ::"l"(p), "r"(x), "r"(y), "r"(z), "r"(w) : "memory"); }
__device__ __forceinline__ void stg32(void* p, uint32_t v) { asm volatile("st.global.u32 [%0], %1;" ::"l"(p), "r"(v) : "memory"); }
__device__ __forceinline__ uint32_t lds32(uint32_t a) { uint32_t v; asm volatile("ld.shared.u32 %0, [%1];" : "=r"(v) : "r"(a) : "memory"); return v; }
__device__ __forceinline__ uint32_t lds16(uint32_t a) { uint16_t v; asm volatile("ld.shared.u16 %0, [%1];" : "=h"(v) : "r"(a) : "memory"); return v; }
__device__ __forceinline__ uint2 lds64(uint32_t a) { uint2 v; asm volatile("ld.shared.v2.u32 {%0,%1}, [%2];" : "=r"(v.x), "=r"(v.y) : "r"(a) : "memory"); return v; }
__device__ __forceinline__ uint4 lds128(uint32_t a) { uint4 v; asm volatile("ld.shared.v4.u32 {%0,%1,%2,%3}, [%4];" : "=r"(v.x), "=r"(v.y), "=r"(v.z), "=r"(v.w) : "r"(a) : "memory"); return v; }
__device__ __forceinline__ float4 lds128f(uint32_t a) { float4 v; asm volatile("ld.shared.v4.f32 {%0,%1,%2,%3}, [%4];" : "=f"(v.x), "=f"(v.y), "=f"(v.z), "=f"(v.w) : "r"(a) : "memory"); return v; }
__device__ __forceinline__ void sts32(uint32_t a, uint32_t v) { asm volatile("st.shared.u32 [%0], %1;" ::"r"(a), "r"(v) : "memory"); }
__device__ __forceinline__ void sts64(uint32_t a, uint32_t x, uint32_t y) { asm volatile("st.shared.v2.u32 [%0], {%1,%2};" ::"r"(a), "r"(x), "r"(y) : "memory"); }
__device__ __forceinline__ void sts128(uint32_t a, uint32_t x, uint32_t y, uint32_t z, uint32_t w) { asm volatile("st.shared.v4.u32 [%0], {%1,%2,%3,%4};" ::"r"(a), "r"(x), "r"(y), "r"(z), "r"(w) : "memory"); }
__device__ __forceinline__ void st_async(uint32_t a, float v, uint32_t bar) {
    asm volatile("st.async.shared::cluster.mbarrier::complete_tx::bytes.f32 [%0], %1, [%2];" ::"r"(a), "f"(v), "r"(bar) : "memory");
}
__device__ __forceinline__ void ldm4(uint32_t a, uint32_t (&r)[4]) {
    asm volatile("ldmatrix.sync.aligned.m8n8.x4.shared.b16 {%0,%1,%2,%3}, [%4];" : "=r"(r[0]), "=r"(r[1]), "=r"(r[2]), "=r"(r[3]) : "r"(a) : "memory");
}
__device__ __forceinline__ void ldm4t(uint32_t a, uint32_t (&r)[4]) {
    asm volatile("ldmatrix.sync.aligned.m8n8.x4.trans.shared.b16 {%0,%1,%2,%3}, [%4];" : "=r"(r[0]), "=r"(r[1]), "=r"(r[2]), "=r"(r[3]) : "r"(a) : "memory");
}
__device__ __forceinline__ void ldm2(uint32_t a, uint32_t& r0, uint32_t& r1) {
    asm volatile("ldmatrix.sync.aligned.m8n8.x2.shared.b16 {%0,%1}, [%2];" : "=r"(r0), "=r"(r1) : "r"(a) : "memory");
}
__device__ __forceinline__ void stm4(uint32_t a, uint32_t r0, uint32_t r1, uint32_t r2, uint32_t r3) {
    asm volatile("stmatrix.sync.aligned.m8n8.x4.shared.b16 [%0], {%1,%2,%3,%4};" ::"r"(a), "r"(r0), "r"(r1), "r"(r2), "r"(r3) : "memory");
}
__device__ __forceinline__ void stm4t(uint32_t a, uint32_t r0, uint32_t r1, uint32_t r2, uint32_t r3) {
    asm volatile("stmatrix.sync.aligned.m8n8.x4.trans.shared.b16 [%0], {%1,%2,%3,%4};" ::"r"(a), "r"(r0), "r"(r1), "r"(r2), "r"(r3) : "memory");
}
__device__ __forceinline__ void stm2t(uint32_t a, uint32_t r0, uint32_t r1) {
    asm volatile("stmatrix.sync.aligned.m8n8.x2.trans.shared.b16 [%0], {%1,%2};" ::"r"(a), "r"(r0), "r"(r1) : "memory");
}
__device__ __forceinline__ void mma_bf(float (&c)[4], const uint32_t (&a)[4], uint32_t b0, uint32_t b1) {
    asm volatile("mma.sync.aligned.m16n8k16.row.col.f32.bf16.bf16.f32 {%0,%1,%2,%3},{%4,%5,%6,%7},{%8,%9},{%0,%1,%2,%3};"
                 : "+f"(c[0]), "+f"(c[1]), "+f"(c[2]), "+f"(c[3]) : "r"(a[0]), "r"(a[1]), "r"(a[2]), "r"(a[3]), "r"(b0), "r"(b1));
}
__device__ __forceinline__ void mma_h(float (&c)[4], const uint32_t (&a)[4], uint32_t b0, uint32_t b1) {
    asm volatile("mma.sync.aligned.m16n8k16.row.col.f32.f16.f16.f32 {%0,%1,%2,%3},{%4,%5,%6,%7},{%8,%9},{%0,%1,%2,%3};"
                 : "+f"(c[0]), "+f"(c[1]), "+f"(c[2]), "+f"(c[3]) : "r"(a[0]), "r"(a[1]), "r"(a[2]), "r"(a[3]), "r"(b0), "r"(b1));
}
__device__ __forceinline__ void mma_hh(uint32_t (&d)[2], const uint32_t (&c)[2], const uint32_t (&a)[4], uint32_t b0, uint32_t b1) {
    asm volatile("mma.sync.aligned.m16n8k16.row.col.f16.f16.f16.f16 {%0,%1},{%2,%3,%4,%5},{%6,%7},{%8,%9};"
                 : "=r"(d[0]), "=r"(d[1]) : "r"(a[0]), "r"(a[1]), "r"(a[2]), "r"(a[3]), "r"(b0), "r"(b1), "r"(c[0]), "r"(c[1]));
}
__device__ __forceinline__ uint32_t pack_bf(float lo, float hi) { uint32_t r; asm("cvt.rn.bf16x2.f32 %0, %1, %2;" : "=r"(r) : "f"(hi), "f"(lo)); return r; }
__device__ __forceinline__ uint32_t pack_h(float lo, float hi) { uint32_t r; asm("cvt.rn.f16x2.f32 %0, %1, %2;" : "=r"(r) : "f"(hi), "f"(lo)); return r; }
__device__ __forceinline__ float bf_lo(uint32_t w) { return __uint_as_float(w << 16); }
__device__ __forceinline__ float bf_hi(uint32_t w) { return __uint_as_float(w & 0xFFFF0000u); }
__device__ __forceinline__ float bf_round(float x) { return __uint_as_float(pack_bf(0.f, x)); }
__device__ __forceinline__ uint32_t bsub(uint32_t a, uint32_t b) { uint32_t r; asm("sub.rn.bf16x2 %0, %1, %2;" : "=r"(r) : "r"(a), "r"(b)); return r; }
__device__ __forceinline__ uint32_t bmul(uint32_t a, uint32_t b) { uint32_t r; asm("mul.rn.bf16x2 %0, %1, %2;" : "=r"(r) : "r"(a), "r"(b)); return r; }
__device__ __forceinline__ uint32_t bfma(uint32_t a, uint32_t b, uint32_t c) { uint32_t r; asm("fma.rn.bf16x2 %0, %1, %2, %3;" : "=r"(r) : "r"(a), "r"(b), "r"(c)); return r; }
__device__ __forceinline__ uint32_t hadd(uint32_t a, uint32_t b) { uint32_t r; asm("add.rn.f16x2 %0, %1, %2;" : "=r"(r) : "r"(a), "r"(b)); return r; }
__device__ __forceinline__ uint32_t hmul(uint32_t a, uint32_t b) { uint32_t r; asm("mul.rn.f16x2 %0, %1, %2;" : "=r"(r) : "r"(a), "r"(b)); return r; }
__device__ __forceinline__ uint32_t hfma(uint32_t a, uint32_t b, uint32_t c) { uint32_t r; asm("fma.rn.f16x2 %0, %1, %2, %3;" : "=r"(r) : "r"(a), "r"(b), "r"(c)); return r; }
__device__ __forceinline__ uint32_t prmt(uint32_t a, uint32_t b, uint32_t s) { uint32_t r; asm("prmt.b32 %0, %1, %2, %3;" : "=r"(r) : "r"(a), "r"(b), "r"(s)); return r; }
__device__ __forceinline__ uint32_t settag(uint32_t v, uint32_t tag) { uint32_t r; asm("lop3.b32 %0, %1, %2, 1, 0xD8;" : "=r"(r) : "r"(v), "r"(tag)); return r; }
__device__ __forceinline__ float ex2f(float x) { float r; asm("ex2.approx.ftz.f32 %0, %1;" : "=f"(r) : "f"(x)); return r; }
__device__ __forceinline__ float rcpf(float x) { float r; asm("rcp.approx.ftz.f32 %0, %1;" : "=f"(r) : "f"(x)); return r; }
__device__ __forceinline__ float sqrt_ap(float x) { float r; asm("sqrt.approx.ftz.f32 %0, %1;" : "=f"(r) : "f"(x)); return r; }
__device__ __forceinline__ float silu_f(float x) { return x * rcpf(1.f + ex2f(-1.4426950408889634f * x)); }
__device__ __forceinline__ float silu_half(float h) { float r; asm("tanh.approx.f32 %0, %1;" : "=f"(r) : "f"(h)); return fmaf(h, r, h); }
__device__ __forceinline__ uint32_t clk32() { uint32_t c; asm volatile("mov.u32 %0, %%clock;" : "=r"(c)); return c; }
__device__ __forceinline__ void spin_until(uint32_t t) {
    asm volatile("{\n.reg .pred p;\n.reg .s32 c;\nLS:\nnanosleep.u32 20;\nmov.u32 c, %%clock;\nsub.s32 c, c, %0;\nsetp.lt.s32 p, c, 0;\n@p bra.uni LS;\n}" ::"r"(t) : "memory");
}
__device__ __forceinline__ void wait_flag(const void* p, uint32_t v) {
    asm volatile("{\n.reg .pred p;\n.reg .u32 c, n;\nmov.u32 n, 32768;\nLF:\nld.relaxed.gpu.global.u32 c, [%0];\nadd.u32 n, n, -1;\nsetp.ne.u32 p, n, 0;\n"
                 "setp.ne.and.u32 p, c, %1, p;\nvote.sync.any.pred p, p, 0xffffffff;\n@p bra.uni LF;\n}" ::"l"(p), "r"(v) : "memory");
}
__device__ __forceinline__ void stg128_if0(uint32_t c, void* p, uint32_t x, uint32_t y, uint32_t z, uint32_t w) {
    asm volatile("{.reg .pred q; setp.eq.u32 q, %5, 0; @q st.global.v4.u32 [%0], {%1,%2,%3,%4};}" ::"l"(p), "r"(x), "r"(y), "r"(z), "r"(w), "r"(c) : "memory");
}
__device__ __forceinline__ uint32_t movm(uint32_t v) { uint32_t r; asm volatile("movmatrix.sync.aligned.m8n8.trans.b16 %0, %1;" : "=r"(r) : "r"(v)); return r; }
__device__ __forceinline__ void cp16(uint32_t dst, const void* src) { asm volatile("cp.async.cg.shared.global [%0], [%1], 16;" ::"r"(dst), "l"(src) : "memory"); }
__device__ __forceinline__ void fence_async() { asm volatile("fence.proxy.async.shared::cta;" ::: "memory"); }
__device__ __forceinline__ uint32_t stale(uint32_t bad, uint32_t v, uint32_t tag) { uint32_t r; asm("lop3.b32 %0, %1, %2, %3, 0xF6;" : "=r"(r) : "r"(bad), "r"(v), "r"(tag)); return r; }
template <int M = 1>
__device__ __forceinline__ bool retry(uint32_t bad, int& it) {
    uint32_t r;
    asm volatile("{.reg .pred p; .reg .b32 b; and.b32 b, %2, %3; add.s32 %1, %1, -1; setp.ne.u32 p, b, 0; setp.gt.and.s32 p, %1, 0, p; vote.sync.any.pred p, p, 0xffffffff; selp.u32 %0, 1, 0, p;}"
                 : "=r"(r), "+r"(it) : "r"(bad), "n"(M));
    return r;
}
template <int N, int STEP>
__device__ __forceinline__ void poll(uint4 (&v)[N], const char* src, uint32_t tag) {
    int it = SPIN_LIMIT;
    bool again;
#pragma unroll 1
    do {
        uint32_t bad = 0;
#pragma unroll
        for (int k = 0; k < N; k++) v[k] = ld_rlx4(src + k * STEP);
#pragma unroll
        for (int k = 0; k < N; k++) bad = stale(bad, v[k].x, tag);
        again = retry(bad, it);
    } while (again);
}

struct cf { float x, y; };
__device__ __forceinline__ cf cmul(cf a, cf b) { return {a.x * b.x - a.y * b.y, a.x * b.y + a.y * b.x}; }
__device__ __forceinline__ cf csq(cf a) { return {a.x * a.x - a.y * a.y, (a.x + a.x) * a.y}; }
__device__ __forceinline__ cf cexp2(float zr2, float zi) {
    const float mag = ex2f(zr2);
    return {mag * __cosf(zi), mag * __sinf(zi)};
}
__device__ __forceinline__ __half2 as_h2(uint32_t v) { return *reinterpret_cast<__half2*>(&v); }
__device__ __forceinline__ uint32_t as_u32(__half2 v) { return *reinterpret_cast<uint32_t*>(&v); }
struct hm { uint32_t v, s; };
__device__ __forceinline__ hm mk_hm(cf a) { return {pack_h(a.x, a.y), pack_h(-a.y, a.x)}; }
__device__ __forceinline__ uint32_t operator*(uint32_t x, hm y) {
    const __half2 xx = as_h2(x);
    return as_u32(__hfma2(__high2half2(xx), as_h2(y.s), __hmul2(__low2half2(xx), as_h2(y.v))));
}
struct KParams { uint32_t are, aim, bre, bim, cre, cim, ldt; };

__device__ __forceinline__ void kgen(const KParams& kp, uint32_t scr, uint32_t l16) {
    const float dt = bf_round(ex2f(bf_lo(kp.ldt) * 1.4426950408889634f));
    cf w = cmul({bf_lo(kp.cre), bf_lo(kp.cim)}, {dt * bf_lo(kp.bre), dt * bf_lo(kp.bim)});
    const uint32_t eb = min(max(__reduce_max_sync(~0u, __float_as_uint(fmaxf(fabsf(w.x), fabsf(w.y)))) & 0x7F800000u, 0x00800000u), 0x7E000000u);
    const float sc = __uint_as_float(0x7F000000u - eb);
    w.x *= sc; w.y *= sc;
    const uint32_t k0 = pack_h(0.f, (float)__reduce_add_sync(~0u, __float2int_rn(w.x * 16777216.f)) * (1.f / 16777216.f));
    const float zr = dt * bf_lo(kp.are) * 1.4426950408889634f, zi = dt * bf_lo(kp.aim);
    const uint32_t st0 = l16 ^ ((l16 >> 3) & 48), st1 = st0 ^ 64, lb = (st0 & 112) + 8 * (l16 & 112), la = 8 * (l16 & 240) + ((l16 ^ (l16 >> 4)) & 112);
    auto st = [&](int row, uint32_t a, uint32_t b, uint32_t c, uint32_t e) { stm4(((row & 4) ? st1 : st0) + scr + row * 128, a, b, c, e); };
    uint32_t a[4][4], d[5][2];
    {
        const cf a16 = cexp2(16.f * zr, -16.f * zi), a32 = csq(a16), a64 = csq(a32);
        const hm m32 = mk_hm(a32), m64 = mk_hm(a64), m128 = mk_hm(csq(a64));
        const uint32_t p1 = pack_h(a16.x, a16.y), p2 = m32.v, p3 = p1 * m32, p5 = p1 * m64, p6 = p2 * m64, p7 = p3 * m64;
        st(0, 0x00003C00u, p1, p2, p3);
        st(4, m64.v, p5, p6, p7);
        st(8, m128.v, p1 * m128, p2 * m128, p3 * m128);
        st(12, m64.v * m128, p5 * m128, p6 * m128, p7 * m128);
        __syncwarp();
#pragma unroll
        for (int k = 0; k < 4; k++) ldm4((la ^ (k * 32)) + scr, a[k]);
    }
    auto tile = [&](int T, int row) {
        d[T][0] = d[T][1] = 0u;
#pragma unroll
        for (int k = 0; k < 2; k++) {
            uint32_t b[4];
            ldm4((lb ^ (k * 64)) + scr + row * 128, b);
            mma_hh(d[T], d[T], a[2 * k], b[0], b[1]);
            mma_hh(d[T], d[T], a[2 * k + 1], b[2], b[3]);
        }
    };
    const cf a1 = cexp2(zr, zi), a2 = csq(a1), a4 = csq(a2), u1 = cmul(w, a1);
    const hm m1 = mk_hm(a1), m2 = mk_hm(a2), m4 = mk_hm(a4), m8 = mk_hm(csq(a4));
    uint32_t v[17], e[9];
    v[1] = pack_h(u1.x, u1.y);
    v[2] = v[1] * m1;
    v[3] = v[1] * m2; v[4] = v[2] * m2;
#pragma unroll
    for (int i = 1; i <= 4; i++) v[4 + i] = v[i] * m4;
#pragma unroll
    for (int i = 1; i <= 8; i++) v[8 + i] = v[i] * m8;
    const cf a256 = cexp2(256.f * zr, 256.f * zi), a512 = csq(a256);
    const hm m256 = mk_hm(a256), m512 = mk_hm(a512), m1024 = mk_hm(csq(a512));
#pragma unroll
    for (int i = 1; i <= 8; i++) e[i] = v[2 * i] * m256;
    __syncwarp();
    st(0, v[1], v[2], v[5], v[6]);
    st(4, v[9], v[10], v[13], v[14]);
    st(8, v[3], v[4], v[7], v[8]);
    st(12, v[11], v[12], v[15], v[16]);
    st(16, e[1], e[2], e[3], e[4]);
    st(20, e[5], e[6], e[7], e[8]);
    __syncwarp();
    tile(0, 0); tile(1, 8); tile(2, 16);
    const uint32_t f8 = v[8] * m512, f16 = v[16] * m512, g8 = e[4] * m512, g16 = e[8] * m512;
    __syncwarp();
    st(0, v[4] * m512, f8, v[12] * m512, f16);
    st(4, e[2] * m512, g8, e[6] * m512, g16);
    st(8, v[8] * m1024, v[16] * m1024, e[4] * m1024, e[8] * m1024);
    st(12, f8 * m1024, f16 * m1024, g8 * m1024, g16 * m1024);
    __syncwarp();
    tile(3, 0); tile(4, 8);
    __syncwarp();
    sts128(scr + l16, d[2][0], d[2][1], k0, eb);
    sts128(scr + l16 + 512, d[0][0], d[1][0], d[0][1], d[1][1]);
    sts128(scr + l16 + 1024, d[3][0], d[3][1], d[4][0], d[4][1]);
}

__device__ __forceinline__ void ktables(uint32_t tab, int far, int lane) {
    uint4 c[4], v[4];
#pragma unroll
    for (int q = 0; q < 4; q++) { c[q] = lds128(tab + T_B3 + q * KG_SCR + lane * 16); v[q] = lds128(tab + T_B3 + q * KG_SCR + lane * 16 + 512 + 512 * far); }
    const uint32_t eb = max(max(c[0].w, c[1].w), max(c[2].w, c[3].w));
    const float rs = __uint_as_float(0x7F000000u - eb);
    uint32_t s[7] = {0u, 0u, 0u, 0u, 0u, 0u, 0u};
#pragma unroll
    for (int q = 0; q < 4; q++) {
        const float ff = __uint_as_float(c[q].w) * rs;
        const uint32_t f = pack_h(ff, ff);
        s[0] = hfma(v[q].x, f, s[0]); s[1] = hfma(v[q].y, f, s[1]); s[2] = hfma(v[q].z, f, s[2]); s[3] = hfma(v[q].w, f, s[3]);
        s[4] = hfma(c[q].x, f, s[4]); s[5] = hfma(c[q].y, f, s[5]); s[6] = hfma(c[q].z, f, s[6]);
    }
    if (far) {
        const int g = lane >> 2, t = lane & 3;
        const uint32_t a4 = tab + T_W4 + 4 * (14 + 2 * g + 32 * (t >> 1) + (t & 1)), a8 = tab + T_W8 + 4 * (7 + g + 16 * t);
        const uint32_t k1 = hmul(s[1], 0x20002000u);
        sts32(a4, hmul(s[0], 0x20002000u)); sts32(a4 + 64, k1);
        sts32(a8, hmul(s[2], 0x20002000u)); sts32(a8 + 32, hmul(s[3], 0x20002000u));
        if (lane == 31) sts64(tab + T_INV, prmt(eb + 0x00800000u, 0u, 0x3232), prmt(k1, 0u, 0x3232));
    } else {
        const uint32_t o = tab + 32 + lane * 16;
        const bool last = lane == 31;
        const uint32_t q0 = __shfl_sync(~0u, last ? s[6] : s[1], lane - 1), q1 = __shfl_sync(~0u, last ? s[1] : s[3], lane - 1);
        const uint32_t q2 = __shfl_sync(~0u, last ? s[3] : s[4], lane - 1), q3 = __shfl_sync(~0u, last ? s[4] : s[5], lane - 1);
        sts128(o, prmt(s[0], q0, 0x7610), prmt(s[0], 0u, 0x1032), prmt(s[1], s[0], 0x7610), prmt(s[1], 0u, 0x1032));
        sts128(o + 512, prmt(s[2], q1, 0x7610), prmt(s[2], 0u, 0x1032), prmt(s[3], s[2], 0x7610), prmt(s[3], 0u, 0x1032));
        sts128(o + 1024, prmt(q2, 0u, 0x3232), prmt(s[4], q2, 0x7610), prmt(s[4], 0u, 0x1032), prmt(s[4], 0u, 0x3232));
        const uint32_t aa = prmt(s[5], 0u, 0x3232);
        sts128(o + 1536, prmt(q3, 0u, 0x3232), prmt(s[5], q3, 0x7610), prmt(s[5], 0u, 0x1032), aa);
        if (last) { sts128(o + 1552, aa, aa, s[5] & 0xFFFF0000u, 0u); sts32(tab + 28, s[6] >> 16); }
    }
}

__device__ __forceinline__ void boxes(uint32_t slot, uint32_t r0, int n, uint4 lt, uint32_t l16) {
    uint32_t xi = slot + 544 * r0, o = slot + 512 * r0 + l16;
    sts128(lt.w + slot, 0u, 0u, 0u, 0u);
#pragma unroll 1
    do {
        const uint2 pv = lds64(lt.x + xi);
        const uint4 ow = lds128(lt.y + xi), nx = lds128(lt.z + xi);
        const uint32_t P[9] = {pv.x, pv.y, ow.x, ow.y, ow.z, ow.w, nx.x, nx.y, nx.z};
        uint32_t Q[8], S2[8], S4[6], b5[5];
#pragma unroll
        for (int k = 0; k < 8; k++) { Q[k] = prmt(P[k], P[k + 1], 0x5432); S2[k] = hadd(P[k], Q[k]); }
#pragma unroll
        for (int k = 0; k < 6; k++) S4[k] = hadd(S2[k], S2[k + 1]);
#pragma unroll
        for (int k = 0; k < 5; k++) b5[k] = hadd(S4[k + 1], P[k + 3]);
        const uint32_t b30 = hadd(Q[3], S2[4]);
        sts128(o + T_B3 + 16, b30, hadd(Q[4], S2[5]), hadd(Q[5], S2[6]), hadd(Q[6], S2[7]));
        sts128(o + T_B5 + 16, b5[0], b5[1], b5[2], b5[3]);
        if (n > 1) {
            sts128(o + T_B7 + 16, hadd(hadd(Q[0], S2[1]), S4[2]), hadd(hadd(Q[1], S2[2]), S4[3]), hadd(hadd(Q[2], S2[3]), S4[4]), hadd(b30, S4[5]));
            sts128(o + T_B9 + 16, hadd(S4[0], b5[1]), hadd(S4[1], b5[2]), hadd(S4[2], b5[3]), hadd(S4[3], b5[4]));
            sts128(lt.z + xi + (T_S2 - T_X), S2[4], S2[5], S2[6], S2[7]);
        }
        xi += 1088; o += 1024;
        asm volatile("" : "+r"(n));
    } while (--n);
}

#define CT(i)
__device__ __forceinline__ void conv_far(uint32_t slot, int nb, uint32_t fbar, bool all, uint32_t tb) {
    const uint4 lb = lds128(tb + 512);
    const uint32_t wa = lds32(tb + 1032) + slot;
    uint2 w4[10];
    uint32_t w8[8][2], f[12][2];
#pragma unroll
    for (int s = 0; s < 10; s++) w4[s] = lds64(lb.w + slot + 32 * s);
#pragma unroll
    for (int k = 0; k < 12; k++) f[k][0] = f[k][1] = 0u;
    auto it = [&](int i) {
        uint32_t q[3][4];
        ldm4t(lb.x + slot + 256 * i, q[0]);
        if (i >= 4) ldm4t(lb.y + slot + 256 * (i - 4), q[2]);
        ldm4t(lb.x + slot + 256 * i + 128, q[1]);
#pragma unroll
        for (int k = i; k < min(i + 5, 12); k++) mma_hh(f[k], f[k], q[0], w4[1 + 2 * (k - i)].x, w4[1 + 2 * (k - i)].y);
        if (i >= 4) {
#pragma unroll
            for (int k = i; k < 12; k++) mma_hh(f[k], f[k], q[2], w8[k - i][0], w8[k - i][1]);
        }
#pragma unroll
        for (int k = i; k < min(i + 5, 12); k++) mma_hh(f[k], f[k], q[1], w4[2 * (k - i)].x, w4[2 * (k - i)].y);
        if (i & 1) stm4t(lb.z + slot + 272 * (i - 1), f[i - 1][0], f[i - 1][1], f[i][0], f[i][1]);
    };
    bar_sync(nb, 64);
    CT(0);
#pragma unroll
    for (int i = 0; i < 4; i++) it(i);
#pragma unroll
    for (int s = 0; s < 8; s++) { w8[s][0] = lds32(wa + 32 * s); w8[s][1] = lds32(wa + 32 * s + 16); }
    mbar_arrive(fbar);
    CT(1);
    if (all) {
#pragma unroll
        for (int i = 4; i < 12; i++) it(i);
        mbar_arrive(fbar + 8);
    }
    CT(2);
}

__device__ __forceinline__ void conv_near(uint32_t slot, uint32_t fbar, int H, char* gs, uint32_t yoff, uint32_t ci, uint32_t tb, uint32_t tag, uint32_t z) {
    float acc[8][4];
    const uint4 la = lds128(tb);
    uint32_t xa = la.x + slot + 2176 * H, xb = la.y + slot + 2176 * H, ra = la.z + slot;
    uint32_t q[8][4], r[2][2];
    r[0][0] = lds32(ra + 32); r[0][1] = lds32(ra);
#pragma unroll
    for (int i = 7; i >= 0; i--) ldm4((i ? xa : xb) + 32 * i, q[i]);
    auto step = [&](int s) {
        r[~s & 1][0] = lds32(ra + 64 * s + 96); r[~s & 1][1] = lds32(ra + 64 * s + 64);
        mma_h(acc[7], q[(7 - s) & 7], r[s & 1][0], r[s & 1][1]);
        q[(7 - s) & 7][3] = q[(8 - s) & 7][0] | z;
        ldm2(s == 7 ? xb - 272 : xa - 48 - 32 * s - (s & 8) * 2, q[(7 - s) & 7][0], q[(7 - s) & 7][1]);
#pragma unroll
        for (int i = 6; i >= 0; i--) mma_h(acc[i], q[(i - s) & 7], r[s & 1][0], r[s & 1][1]);
        q[(7 - s) & 7][2] = q[(7 - s) & 7][1] | z;
    };
#pragma unroll
    for (int i = 0; i < 8; i++) acc[i][0] = acc[i][1] = acc[i][2] = acc[i][3] = 0.f;
    step(0);
    CT(0);
#pragma unroll 1
    for (int n = 0; n < 4; n++) {
#pragma unroll
        for (int s = 1; s <= 8; s++) step(s);
        xa -= 272; xb -= 272; ra += 512;
    }
    CT(1);
    const uint4 lc = lds128(tb + 1024);
    const uint2 ik = lds64(slot + T_INV);
    const uint32_t aa = (H ? lc.y : lc.x) + slot, b1 = lc.w, b0 = hmul(b1, ik.y), inv = ik.x;
    char* yo = gs + (la.w + yoff);
    mbar_wait(fbar + 8 * H);
    CT(2);
    asm volatile("{.reg .pred p; setp.eq.u32 p, %1, 0; @p red.relaxed.gpu.global.add.u32 [%0], 1;}" ::"l"(gs + G_CNT + (ci + la.w)), "r"(la.w) : "memory");
#pragma unroll
    for (int a = 0; a < 4; a++) {
#pragma unroll
        for (int i = 2 * a; i < 2 * a + 2; i++) {
            ldm4(aa + 32 * i, q[i]);
            mma_h(acc[i], q[i], b0, b1);
        }
        stg128(yo + G_Y + a * 36864, settag(bmul(pack_bf(acc[2 * a][0], acc[2 * a][1]), inv), tag), bmul(pack_bf(acc[2 * a][2], acc[2 * a][3]), inv),
               bmul(pack_bf(acc[2 * a + 1][0], acc[2 * a + 1][1]), inv), bmul(pack_bf(acc[2 * a + 1][2], acc[2 * a + 1][3]), inv));
    }
    CT(3);
}

#define LEAVE return
__global__ void __cluster_dims__(2, 1, 1) __launch_bounds__(NTHREADS, 1) fused_kernel(const Hot p, const __grid_constant__ Maps m) {
    extern __shared__ __align__(1024) char smem[];
    const uint32_t t0 = clk32();
    const uint32_t tid = threadIdx.x, lane = tid & 31, bid = blockIdx.x, r = bid & 1, rb = bid >> 1;
    uint32_t c5 = 288 * (bid >> 6) + 256 + (rb & 31), c0 = c5 + (rb & 31) - 192 - 64 * r;
    uint32_t S = smem_u32(smem), l16 = 16 * lane;
    asm volatile("" : "+r"(S), "+r"(l16), "+r"(c0), "+r"(c5));
    const uint32_t warp = __shfl_sync(~0u, tid >> 5, 0), sub = warp & 3, grp = warp >> 2;
    uint32_t tag;
    const uint32_t ns = (bid * 171) >> 11, kq = bid - 12 * ns;
    uint32_t w0 = SM_GU, xs = SM_XS, bar = S + B_W * 8, slice = bid;

    if (bid < NMAIN) {
        if (warp == 16) {
            if (elect()) {
                mbar_init(S + B_ROWS * 8, 1);
                asm volatile("mbarrier.expect_tx.relaxed.cta.shared::cta.b64 [%0], %1;" ::"r"(S + B_ROWS * 8), "n"(32 * ROW + 576) : "memory");
                tma3d(S + SM_ROWS, &m.u, 144 * r, 32 * rb, S + B_ROWS * 8);
                bulk_g2s(S + SM_WR, p.wr + 288 * r, 576, S + B_ROWS * 8);
                mbar_init(S + B_GO * 8, 8); mbar_init(S + B_ST * 8, 8);
                pf_tmap(&m.gu);
            }
            __syncthreads();
            if (elect()) {
                asm volatile("mbarrier.expect_tx.relaxed.cta.shared::cta.b64 [%0], 3648;" ::"r"(S + B_GO * 8) : "memory");
                asm volatile("mbarrier.expect_tx.relaxed.cta.shared::cta.b64 [%0], 3072;" ::"r"(S + (B_K + 4) * 8) : "memory");
                asm volatile("mbarrier.expect_tx.relaxed.cta.shared::cta.b64 [%0], 1024;" ::"r"(S + B_ST * 8) : "memory");
                asm volatile("fence.mbarrier_init.release.cluster;" ::: "memory");
            }
            __syncwarp();
            asm volatile("barrier.cluster.arrive.relaxed.aligned;" ::: "memory");
            tag = ld_rlx(p.epoch);
            sts32(S + SM_TAG, tag);
            if (r) *(uint2*)(p.s + G_KEY + (256 * rb + 8 * lane)) = make_uint2(~tag, 0u);
            mbar_arrive(S + B_ROWS * 8);
            TS(0);
            spin_until(t0 + TN(t_w));
            const CUtensorMap* mp = &m.gu;
            int col = 16 * bid, row = 0;
            uint32_t dst = S + SM_GU;
            if (elect()) { bulk_g2s(S + SM_TAB, p.tab, 3072, S + B_GO * 8); bulk_g2s(S + SM_DSK, p.dskip + 288 * r, 576, S + B_GO * 8); }
#pragma unroll 1
            for (int s = 0; s < 15; s++) {
                const int w = s < TN(n_w) ? TN(w1) : TN(w2);
                if (s >= w) mbar_wait(bar - w * 8);
                if (s == 9) {
                    if (bid >= NDOWN) break;
                    TS(2);
                    mbar_wait(S + B_FREE * 8);
                    col = 32 * ns; row = 384 * kq; mp = &m.wd; dst = S + SM_GU;
                }
                if (elect()) {
                    mbar_expect(bar, STAGE);
                    tma3d(dst, mp, col, row, bar);
                }
                dst += STAGE; row += 64; bar += 8;
            }
            TS(1);
            LEAVE;
        }

        const uint32_t gq = grp >> 2, bi = sub - gq, ck = bi + (r & gq) * 2;
        KParams kp;
        if (warp != 19) {
            const uint32_t ko = (gq ? c5 : c0 + 64 * (grp & 2) + (grp & 1)) * 128 + 32 * ck + lane;
            kp.are = ldg16(p.are + ko); kp.aim = ldg16(p.aim + ko); kp.bre = ldg16(p.bre + ko);
            kp.bim = ldg16(p.bim + ko); kp.cre = ldg16(p.cre + ko); kp.cim = ldg16(p.cim + ko);
            kp.ldt = ldg16(p.logdt + (ko >> 7));
        }
        if (grp & 2) {
            if (elect()) {
#pragma unroll
                for (int i = 0; i < 6; i++) mbar_init(S + 48 * (warp - 8) + 8 * i, warp < 11 ? 4 : 1);
            }
#pragma unroll 1
            for (uint32_t i = 16 * tid - 4096; i < T_X; i += 4096)
#pragma unroll
                for (int k = 0; k < 5; k++) sts128(S + SM_SLOT + k * SLOT + i, 0u, 0u, 0u, 0u);
            if (tid >= 476) sts128(S + SM_ONES + 16 * (tid - 476), 0x3F803F80u, 0x3F803F80u, 0x3F803F80u, 0x3F803F80u);
        }
        __syncthreads();
        asm volatile("barrier.cluster.arrive.relaxed.aligned;" ::: "memory");
        if (grp >= 2) {
            asm volatile("barrier.cluster.wait.aligned;" ::: "memory");
            if (!gq) {
                const uint32_t t = lane & 3, pa = S + SM_PART + 1024 * r + 128 * (warp - 8) + 4 * (lane & 28);
                const uint32_t ad = S + ((lane & 8) ? ((lane & 7) ? SM_WR : SM_ONES) : SM_ROWS + ROW * (8 * sub + (lane & 7))) + 288 * (grp & 1) + (lane & 16);
                float d[3][4];
#pragma unroll
                for (int i = 0; i < 3; i++) d[i][0] = d[i][1] = d[i][2] = d[i][3] = 0.f;
                mbar_wait(S + B_ROWS * 8);
                TS(0);
#pragma unroll
                for (int k = 0; k < 9; k++) {
                    uint32_t a[4];
                    ldm4(ad + 32 * k, a);
                    mma_bf(d[k % 3], a, a[0], a[2]);
                }
#pragma unroll
                for (int i = 0; i < 4; i++) d[0][i] += d[1][i] + d[2][i];
                const float s0 = __shfl_sync(~0u, d[0][2], t), s1 = __shfl_sync(~0u, d[0][3], t), w1 = __shfl_sync(~0u, d[0][2], t + 4);
                const bool odd = lane & 4;
                const float q = odd ? d[0][1] : d[0][0], s = odd ? s1 : s0, w = odd ? d[0][3] : w1;
                asm volatile("{.reg .pred p; setp.eq.u32 p, %0, %1;\n"
                             "@p st.async.shared::cluster.mbarrier::complete_tx::bytes.v4.f32 [%2], {%5,%6,%7,%8}, [%3];\n"
                             "@p st.shared.v4.f32 [%4], {%5,%6,%7,%8};}"
                             ::"r"(lane >> 3), "r"(t), "r"(pa ^ (1u << 24)), "r"((S ^ (1u << 24)) + B_ST * 8), "r"(pa), "f"(q), "f"(s), "f"(w), "f"(w1) : "memory");
                mbar_arrive(S + B_ST * 8);
                const uint32_t tg = lds32(S + SM_TAG + (l16 >> 9));
                uint32_t xa = S + SM_ROWS + 37 * l16 + 16 * (warp - 8), x[4];
                ldm4t(xa, x);
                mbar_wait(S + B_ST * 8);
                TS(1);
                float4 v[4];
#pragma unroll
                for (int i = 0; i < 4; i++) v[i] = lds128f(S + SM_PART + 512 * i + l16);
                const float mean = ((v[0].y + v[1].y) + (v[2].y + v[3].y)) * (1.f / 576.f);
                const float var = fmaxf(((v[0].x + v[1].x) + (v[2].x + v[3].x)) * (1.f / 576.f) - mean * mean, 0.f);
                const uint32_t ms = pack_bf(mean, sqrt_ap(bf_round(bf_round(var) + 1e-5f)));
                const float ri = 0.5f * rcpf(bf_hi(ms));
                sts64(S + SM_STAT + 8 * lane, __float_as_uint(ri), __float_as_uint(-bf_lo(ms) * ri));
                if (warp + r == 16) *(uint2*)(p.s + G_KEY + (256 * rb + 8 * lane)) = make_uint2(settag(__float_as_uint((v[0].z + v[1].z) + (v[2].z + v[3].z)), tg), ms);
                __syncwarp();
#pragma unroll
                for (int i = 0; i < 4; i++) v[i] = lds128f(S + SM_STAT + 64 * i + (l16 & 48));
                uint32_t xo = G_X + (144 * r + 4 * (warp - 8) + (lane >> 3)) * 8192 + 128 * rb + (l16 & 112);
#pragma unroll 1
                for (int b = grp & 1; b < 5; b++) {
                    float f[8];
#pragma unroll
                    for (int i = 0; i < 4; i++) { f[2 * i] = bf_lo(x[i]); f[2 * i + 1] = bf_hi(x[i]); }
                    xa += 128;
                    ldm4t(xa, x);
                    uint32_t o[4];
#pragma unroll
                    for (int i = 0; i < 4; i++) o[i] = pack_h(fmaf(f[2 * i], v[i].x, v[i].y), fmaf(f[2 * i + 1], v[i].z, v[i].w));
                    stg128(p.s + xo, settag(o[0], tg), o[1], o[2], o[3]);
                    xo += 32 * 8192;
                }
                mbar_arrive(S + B_GO * 8);
                TS(2);
            } else if (TN(late)) {
                mbar_wait(S + (TN(late) == 1 ? B_ST : TN(late) == 2 ? B_GO : B_K) * 8);
            }
        }
        if (warp != 19) {
            const uint32_t slot = S + SM_SLOT + grp * SLOT, scr = slot + T_B3 + ck * KG_SCR;
            kgen(kp, scr, l16);
            TS(4);
            if (gq) {
                fence_async();
                __syncwarp();
                if (elect())
                    asm volatile("cp.async.bulk.shared::cluster.shared::cta.mbarrier::complete_tx::bytes [%0], [%1], 1536, [%2];"
                                 ::"r"(scr ^ (1u << 24)), "r"(scr), "r"((S ^ (1u << 24)) + (B_K + 4) * 8) : "memory");
            }
            mbar_arrive(S + (B_K + grp) * 8, 1 + gq);
            if ((0x6F033u >> warp) & 1) {
                const uint32_t ts = grp - (bi >> 1);
                mbar_wait(S + (B_K + ts) * 8);
                ktables(S + SM_SLOT + ts * SLOT, bi & 1, lane);
                mbar_arrive(S + (B_T + ts) * 8, 2);
                TS(5);
            }
        }
        mbar_wait(S + B_GO * 8);
        tag = lds32(S + SM_TAG + (l16 >> 9));
        if (grp < 2) {
            const uint4 lr = lds128(S + SM_TAB + 2048 + l16);
            const char* src = p.s + G_X + (lr.x + (c0 + 128 * grp) * 4096 + 2048 * sub);
            const char* sr5 = p.s + G_X + (lr.z + (c5 >> 1) * 8192 + 64 * (c5 & 1) + 128 * sub);
            const uint32_t now = clk32();
            spin_until(now + max((int)(t0 + TN(t_x) - now), 0) + (grp ? TN(d_x2) : TN(d_x)));
            uint4 u[6];
            int it = SPIN_LIMIT;
            bool again;
            u[4].x = u[5].x = tag;
#pragma unroll 1
            do {
                uint32_t bad = 0;
#pragma unroll
                for (int k = 0; k < 6; k++)
                    if (k < 4 || grp) u[k] = ld_rlx4(k < 4 ? src + 128 * k : sr5 + 4096 * (k - 4));
#pragma unroll
                for (int k = 0; k < 6; k++) bad = stale(bad, u[k].x, tag);
                again = retry(bad, it);
            } while (again);
#pragma unroll
            for (int k = 0; k < 6; k++)
                if (k < 4 || grp)
                    stm4(k < 4 ? lr.y + S + SM_SLOT + 2 * SLOT * grp + 1088 * sub + 64 * k : lr.w + S + SM_SLOT + 4 * SLOT + 2176 * (k - 4) + 64 * sub, u[k].x, u[k].y, u[k].z, u[k].w);
            mbar_arrive(S + (B_X + grp) * 8);
            TS(6);
        }
        if (grp != 3) {
            if (warp != 19) {
                const uint32_t sl = __shfl_sync(~0u, warp == 8 ? 4 : gq ? 4 * bi : sub, 0), slot = S + SM_SLOT + sl * SLOT, fb = S + B_F * 8 + 16 * sl, tb = S + SM_TAB + l16;
                const bool far = warp > 8, all = sl + r < 5;
                const uint4 lt = lds128(tb + 1536);
                mbar_wait(S + (B_T + sl) * 8);
                mbar_wait(S + (B_X + (sl >= 2)) * 8);
                TS(9);
                if (grp) boxes(slot, far, all ? 3 : 1, lt, l16);
                TS(8);
                if (far) {
                    conv_far(slot, 1 + sl, fb, all, tb);
                    TS(7);
                } else {
                    if (grp) bar_arrive(1 + sl, 64);
                    const uint32_t ch = sl == 4 ? c5 : c0 + 64 * (sl & 2) + (sl & 1), H = grp && all;
                    conv_near(slot, fb, H, p.s, 32 * 36864 * H + 64 * ch, 8 * (ch & ~31u) + 128 * H, tb, tag, p.zero);
                    mbar_arrive(S + (B_DONE + grp) * 8);
                    TS(7);
                }
                if ((0x60170u >> warp) & 1) LEAVE;
            }
            const uint32_t oc = 64 * __popc(0xE8Fu << (31 - min(warp, 12u)) << 1);
            const uint4 lo = lds128(S + SM_TAB + 2560 + l16);
            uint32_t cc[4][4], gt[4][4], xa = lo.x + S + oc, sa = lo.y + S;
            uint4 dk = lds128(S + SM_DSK + oc + (l16 & 48));
            dk.x = bmul(dk.x, 0x40004000u); dk.y = bmul(dk.y, 0x40004000u); dk.z = bmul(dk.z, 0x40004000u); dk.w = bmul(dk.w, 0x40004000u);
#pragma unroll PRE_UNROLL
            for (int i = 0; i < 4; i++) {
                const uint4 x4 = lds128(xa);
                const uint2 st = lds64(sa);
                const uint32_t x[4] = {x4.x, x4.y, x4.z, x4.w}, d[4] = {dk.x, dk.y, dk.z, dk.w};
#pragma unroll
                for (int b = 0; b < 4; b++) {
                    const float h0 = fmaf(bf_lo(x[b]), __uint_as_float(st.x), __uint_as_float(st.y)), h1 = fmaf(bf_hi(x[b]), __uint_as_float(st.x), __uint_as_float(st.y));
#pragma unroll
                    for (int q = 0; q < 3; q++) { cc[q][b] = cc[q + 1][b]; gt[q][b] = gt[q + 1][b]; }
                    gt[3][b] = pack_bf(silu_half(h0), silu_half(h1));
                    cc[3][b] = bfma(bmul(pack_bf(h0, h1), d[b]), gt[3][b], x[b]);
                }
                xa += 8 * ROW; sa += 64;
            }
            char* oa = (char*)p.out + (lo.z + 36864 * rb + 576 * r + oc);
            const char* ya = p.s + G_Y + (lds32(S + SM_TAB + 2048 + l16) + bid * 18432 + 32 * oc);
            mbar_wait(S + B_SEL * 8);
            const uint32_t skip = lds32(S + SM_SKIP) >> lo.w;
            mbar_wait(S + (B_DONE + (bid >> 6)) * 8);
            TS(10);
            wait_flag(p.s + G_CNT + (2304 * r + 4 * oc + 2 * (bid & 64)), 32 * tag);
            TS(11);
            uint4 y[4];
            poll<4, 128>(y, ya, tag);
            TS(12);
#pragma unroll
            for (int i = 0; i < 4; i++) {
                uint32_t o[4];
#pragma unroll
                for (int b = 0; b < 4; b++) o[b] = bfma(movm(i == 0 ? y[b].x : i == 1 ? y[b].y : i == 2 ? y[b].z : y[b].w), gt[i][b], cc[i][b]);
                stg128_if0(skip & (1u << (8 * i)), oa + 9216 * i, o[0], o[1], o[2], o[3]);
            }
            TS(13);
            LEAVE;
        }
    } else {
        tag = ld_rlx(p.epoch + (lane & p.zero));
        if (elect()) {
#pragma unroll
            for (int i = 0; i < 3; i++) mbar_init(S + B_W * 8 + 24 * min(warp, 11) + 8 * i, 1);
            if (warp == 16) { mbar_init(S + B_FREE * 8, 4); mbar_init(S + B_SEL * 8, 4); pf_tmap(&m.gu); }
        }
        __syncthreads();
        if (warp >= 16) {
            if (warp == 16) {
                int col = 64 * bid - 6144, row = 0;
                uint32_t dst = S + SV_GU;
                spin_until(t0 + TN(t_w));
#pragma unroll 1
                for (int s = 0; s < 36; s++) {
                    if (s == TN(n_sv)) mbar_wait(S + B_SEL * 8);
                    const int w = s < TN(n_sv) ? TN(ws1) : TN(ws2);
                    if (s >= w) mbar_wait(S + (B_W + s - w) * 8);
                    if (s == 27) { mbar_wait(S + B_FREE * 8); fence_async(); dst = S + SV_GU; }
                    if (elect()) {
                        mbar_expect(S + (B_W + s) * 8, STAGE);
                        tma3d(dst, &m.gu, col, row, S + (B_W + s) * 8);
                    }
                    dst += STAGE; row += 64;
                    if (row == 576) { row = 0; col += 16; }
                }
            }
            TS(1);
            LEAVE;
        }
        char* xo = p.s + G_XS + (512 * (bid & 3) + l16);
        if (!warp) stg128(xo, ~tag, 0u, 0u, 0u);
        if (tid == 0) sts32(S + SV_CAND, 0u);
        float sw = 0.f;
#pragma unroll
        for (int i = 0; i < 9; i++) { const uint32_t w = __ldg((const uint32_t*)p.wr + 32 * i + lane); sw += bf_lo(w) + bf_hi(w); }
#pragma unroll
        for (int o = 16; o > 0; o >>= 1) sw += __shfl_xor_sync(~0u, sw, o);
        spin_until(t0 + TN(t_key));
        uint4 v[2];
#pragma unroll 1
        for (int it = 0; it < SPIN_LIMIT; it++) {
            v[0] = ld_rlx4((const uint4*)(p.s + G_KEY) + tid); v[1] = ld_rlx4((const uint4*)(p.s + G_KEY) + tid + 512);
            if (!__any_sync(~0u, ((v[0].x ^ tag) | (v[0].z ^ tag) | (v[1].x ^ tag) | (v[1].z ^ tag)) & 1)) break;
        }
        TS(2);
        auto mk = [&](uint32_t dot, uint32_t ms, int row) {
            const uint32_t s = pack_bf(0.f, (__uint_as_float(dot) - bf_lo(ms) * sw) * rcpf(bf_hi(ms)));
            return (((s ^ (((int)s >> 31) | 0x80000000u)) >> 4) & 0x0FFFF000u) | (uint32_t)(4095 - row);
        };
        const uint32_t k[4] = {mk(v[0].x, v[0].y, 2 * tid), mk(v[0].z, v[0].w, 2 * tid + 1), mk(v[1].x, v[1].y, 2 * tid + 1024), mk(v[1].z, v[1].w, 2 * tid + 1025)};
        const uint32_t km[4] = {v[0].y, v[0].w, v[1].y, v[1].w};
        const uint32_t kx = max(max(k[0], k[1]), max(k[2], k[3]));
        const uint32_t wx = __reduce_max_sync(~0u, kx);
        sts32(S + SV_CAND + 16 + 4 * warp, wx);
        if (lane < 9) asm volatile("prefetch.global.L2 [%0];" ::"l"((const char*)p.u + ((4095 - (wx & 4095)) * 1152 + 8 * l16)));
        bar_sync(N_X1, 512);
        TS(5);
        const uint32_t mine = lds32(S + SV_CAND + 16 + 4 * (lane & 15));
        const uint4 o0 = lds128(S + SV_CAND + 16 + 2 * (lane & 16)), o1 = lds128(S + SV_CAND + 32 + 2 * (lane & 16));
        auto gt = [](uint32_t a, uint32_t b) { return (b - a) >> 31; };
        uint32_t rank = (gt(o0.x, mine) + gt(o0.y, mine) + gt(o0.z, mine)) + (gt(o0.w, mine) + gt(o1.x, mine) + gt(o1.y, mine)) + (gt(o1.z, mine) + gt(o1.w, mine));
        rank += __shfl_xor_sync(~0u, rank, 16);
        const uint32_t bound = __reduce_max_sync(~0u, rank == 7 ? mine : 0u);
        if (kx >= bound) {
            uint32_t pos;
            asm volatile("atom.shared.add.u32 %0, [%1], %2;" : "=r"(pos) : "r"(S + SV_CAND + (l16 >> 9)), "r"(32 - 8 * (gt(bound, k[0]) + gt(bound, k[1]) + (gt(bound, k[2]) + gt(bound, k[3])))) : "memory");
#pragma unroll
            for (int q = 0; q < 4; q++)
                if (k[q] >= bound) { sts64(S + SV_XS + pos, k[q], km[q]); pos += 8; }
        }
        bar_sync(N_X1, 512);
        TS(6);
        const int n8 = lds32(S + SV_CAND);
#pragma unroll 1
        for (int i = 8 * warp; i < n8; i += 128) {
            const uint2 c = lds64(S + SV_XS + i);
            const uint32_t row = 4095 - (c.x & 4095), k32 = (c.x << 4) & 0xFFFF0000u, sb = (k32 ^ ((~(int)k32 >> 31) | 0x80000000u)) & 0xFFFF0000u;
            if (lane < 9) asm volatile("prefetch.global.L2 [%0];" ::"l"((const char*)p.u + (row * 1152 + 8 * l16)));
            const uint32_t w = settag(pack_bf(0.f, rcpf(1.f + ex2f(-1.4426950408889634f * __uint_as_float(sb)))) | (row << 1), tag);
            const float ri = rcpf(bf_hi(c.y));
            rank = 0;
            int q = 0;
#pragma unroll 1
            do { rank += __popc(__ballot_sync(~0u, lds32(S + SV_XS + q + 8 * lane) > c.x && q + 8 * (int)lane < n8)); } while ((q += 256) < n8);
            if (rank < 8) sts128(S + SM_REC + 16 * rank, w, prmt(c.y, 0u, 0x1010), row * 1152, __float_as_uint(ri));
        }
        bar_sync(N_X1, 512);
        TS(3);
        if (!warp) { const uint4 rec = lds128(S + SM_REC + (l16 & 112)); stg128(xo, rec.x, rec.y, rec.z, rec.w); }
        TS(4);
        if (grp) mbar_wait(S + B_FREE * 8);
        w0 = SV_GU + (grp % 3) * 9 * STAGE; xs = SV_XS; bar = S + (B_W + 9 * grp) * 8; slice = 4 * bid + grp - 384;
    }

    {
    const uint32_t fi = tid & 127;
    const bool gate = (sub >> 1) == p.swap;
    char* ho = p.s + G_H + (512 * slice + 256 * (sub & 1) + 4 * lane);
    char* po = p.s + G_PART + (((4 * ns + sub) * 12 + kq) * 512 + 128 * (lane & 3) + (lane & 28));
    stg32(ho + 64 * (sub & 2), ~tag);
#pragma unroll
    for (int i = 0; i < 4; i++) stg32(po + 32 * i, ~tag);
    if (bid < NMAIN) {
        __nanosleep(max((int)(t0 + TN(t_xs) - clk32()), 0) >> 1);
        uint4 rec[1];
        poll<1, 0>(rec, p.s + G_XS + (128 * (rb & 15) + (l16 & 112)), tag);
        sts128(S + SM_REC + (l16 & 112), rec[0].x, rec[0].y, rec[0].z, rec[0].w);
        uint32_t bit;
        asm("shl.b32 %0, 1, %1;" : "=r"(bit) : "r"(((rec[0].x >> 1) & 2047) - 32 * rb));
        sts32(S + SM_SKIP, __reduce_or_sync(~0u, bit));
        __syncwarp();
        TS(7);
    }
    float d[4];
#pragma unroll 1
    for (uint32_t ph = 0;; ph = 1) {
        if (bid < NMAIN || !grp) {
            uint4 v[5];
            uint32_t xd = S + SM_XS + 16 * fi + 2 * (fi & 120);
            if (ph) {
                const char* src = p.s + G_H + (6144 * kq + 16 * fi);
                int it = SPIN_LIMIT;
                uint32_t bad;
#pragma unroll 1
                do {
                    __nanosleep(TN(nap));
                    bad = 0;
#pragma unroll
                    for (int k = 0; k < 3; k++) v[k] = ld_rlx4(src + 2048 * k);
#pragma unroll
                    for (int k = 0; k < 3; k++) bad = stale(bad, v[k].x, tag);
                } while (retry(bad, it));
            } else {
                const uint4 rec = lds128(S + SM_REC + 2 * (fi & 56));
                const char* src = (const char*)p.u + (rec.z + (l16 & 112) + 64 * (sub & 2));
                xd = S + xs + 9 * (l16 & 112) + 2 * (fi & 56) + 576 * (sub & 2);
#pragma unroll
                for (int k = 0; k < 5; k++) {
                    if (k < 4 || sub < 2) v[k] = __ldg((const uint4*)(src + 256 * k));
                    v[k] = make_uint4(bsub(v[k].x, rec.y), bsub(v[k].y, rec.y), bsub(v[k].z, rec.y), bsub(v[k].w, rec.y));
                }
                sts128(xd + 3 * 2304, v[3].x, v[3].y, v[3].z, v[3].w);
                if (sub < 2) sts128(xd + 4 * 2304, v[4].x, v[4].y, v[4].z, v[4].w);
                mbar_arrive(S + B_SEL * 8);
            }
#pragma unroll
            for (int k = 0; k < 3; k++) sts128(xd + 2304 * k, v[k].x, v[k].y, v[k].z, v[k].w);
            if (ph) TS(9); else TS(8);
            fence_async();
            bar_sync(N_WG + grp, 128);
        }
        uint32_t da = (((S & 0xFFFF) + w0) >> 4) + (256 << 16), db = (((S & 0xFFFF) + xs) >> 4) + (9 << 16), n = 9 - 3 * ph, ok = 0;
        d[0] = d[1] = d[2] = d[3] = 0.f;
#pragma unroll 1
        do {
            if (bar == S + (B_W + 6) * 8 && grp) {
                asm volatile("wgmma.wait_group.sync.aligned 0;" ::: "memory");
                mbar_arrive(S + B_FREE * 8);
            }
            if (!ok) mbar_wait(bar);
            bar += 8;
            asm volatile("{.reg .pred p; mbarrier.test_wait.parity.shared::cta.b64 p, [%1], 0; selp.u32 %0,1,0,p;}" : "=r"(ok) : "r"(bar) : "memory");
            asm volatile("wgmma.fence.sync.aligned;" ::: "memory");
#pragma unroll
            for (int k = 0; k < 4; k++) wgmma8(d, (0x80000020ull << 32) + da + 64 * k, (uint64_t)db + 18 * k);
            asm volatile("wgmma.commit_group.sync.aligned;" ::: "memory");
            da += STAGE / 16; db += 72;
        } while (--n);
        asm volatile("wgmma.wait_group.sync.aligned 0;" : "+f"(d[0]), "+f"(d[1]), "+f"(d[2]), "+f"(d[3])::"memory");
        if (ph) break;
        TS(10);
        const float r0 = __uint_as_float(lds32(S + SM_REC + 12 + 2 * (l16 & 48))), r1 = __uint_as_float(lds32(S + SM_REC + 28 + 2 * (l16 & 48)));
        const uint32_t ex = S + w0 + 6 * STAGE + 8 * (fi & 63), v0 = pack_bf(d[0] * r0, d[1] * r1), v1 = pack_bf(d[2] * r0, d[3] * r1);
        if (!gate) sts64(ex, v0, v1);
        bar_sync(N_WG + grp, 128);
        if (gate) {
            const uint2 u = lds64(ex);
            const uint32_t h0 = movm(bmul(pack_bf(silu_half(0.5f * bf_lo(v0)), silu_half(0.5f * bf_hi(v0))), u.x));
            const uint32_t h1 = movm(bmul(pack_bf(silu_half(0.5f * bf_lo(v1)), silu_half(0.5f * bf_hi(v1))), u.y));
            stg32(ho, settag(h0, (lane & 3) ? h0 : tag)); stg32(ho + 128, settag(h1, (lane & 3) ? h1 : tag));
        }
        if (!grp) mbar_arrive(S + B_FREE * 8);
        TS(11);
        if (bid >= NDOWN) LEAVE;
    }
#pragma unroll
    for (int i = 0; i < 4; i++) stg32(po + 64 * (i & 1) + 32 * (i >> 1), settag(__float_as_uint(d[i]), tag));
    TS(13);
    if (r && kq < 8) {
        const uint32_t tile = 4 * ns + (kq >> 1), cc = 16 * tile + (tid & 15);
        const uint4 rec = lds128(S + SM_REC + (fi & 112));
        const uint32_t row = (rec.x >> 1) & 2047, oi = (rec.z >> 1) + cc, xr = ldg16(p.u + oi), dk = ldg16(p.dskip + cc);
        const char* ya = p.s + G_Y + ((row >> 5) * 36864 + 64 * cc + 8 * (row & 6));
        const char* pa = p.s + G_PART + (tile * 6144 + 4 * fi);
        const char* fl = p.s + G_CNT + (128 * (tile & ~1u) + 128 * (row >> 10));
        uint32_t w[12], f = ld_rlx(fl);
        uint4 y;
        y.x = ~tag;
        int it = SPIN_LIMIT;
        bool again;
#pragma unroll 1
        do {
            if (f == 32 * tag) y = ld_rlx4(ya);
            f = ld_rlx(fl);
#pragma unroll
            for (int k = 0; k < 12; k++) w[k] = ld_rlx(pa + 512 * k);
            uint32_t bad = y.x ^ tag;
#pragma unroll
            for (int k = 0; k < 12; k++) bad = stale(bad, w[k], tag);
            again = retry(bad, it);
        } while (again);
        float s3[3];
#pragma unroll
        for (int k = 0; k < 3; k++) s3[k] = (__uint_as_float(w[4 * k]) + __uint_as_float(w[4 * k + 1])) + (__uint_as_float(w[4 * k + 2]) + __uint_as_float(w[4 * k + 3]));
        const float x = bf_lo(xr), xn = bf_round(bf_round(x - bf_lo(rec.y)) * __uint_as_float(rec.w));
        const bool hi = row & 16;
        const float sg = fmaf(xn, bf_lo(dk), bf_lo(prmt(hi ? y.z : y.x, hi ? y.w : y.y, 0x10 + 0x22 * (row & 1) + 0x44 * ((row >> 3) & 1))));
        const float up = bf_round(bf_round(s3[0] + s3[1] + s3[2]) * bf_hi(rec.x));
        p.out[oi] = __float2bfloat16(fmaf(sg, silu_half(0.5f * bf_round(xn + up)), x));
        if (bid + fi == 1) stg32(p.epoch, tag + 1);
        TS(14);
    }
    }
    LEAVE;
}

typedef CUresult (*EncodeFn)(CUtensorMap*, CUtensorMapDataType, cuuint32_t, void*, const cuuint64_t*, const cuuint64_t*, const cuuint32_t*,
                             const cuuint32_t*, CUtensorMapInterleave, CUtensorMapSwizzle, CUtensorMapL2promotion, CUtensorMapFloatOOBfill);

void make_map(EncodeFn enc, CUtensorMap* m, const void* base, uint64_t cols, uint64_t rows, uint64_t second, uint32_t bc, uint32_t br, CUtensorMapSwizzle sw) {
    cuuint64_t gd[3] = {cols / 2, rows, second ? 2u : 1u};
    cuuint64_t gs[2] = {cols * 2, second ? second : cols * 2 * rows};
    cuuint32_t bd[3] = {bc / 2, br, second ? 2u : 1u}, es[3] = {1, 1, 1};
    enc(m, CU_TENSOR_MAP_DATA_TYPE_UINT32, 3, const_cast<void*>(base), gd, gs, bd, es, CU_TENSOR_MAP_INTERLEAVE_NONE, sw,
        CU_TENSOR_MAP_L2_PROMOTION_L2_128B, CU_TENSOR_MAP_FLOAT_OOB_FILL_NONE);
}

}

extern "C" void kernel_launch(void* const* d_in, const int* in_sizes, int n_in, void* d_out, int out_size) {
    static EncodeFn enc = nullptr;
    static char* gs = nullptr;
    static LaneTab* gt = nullptr;
    static uint32_t* ge = nullptr;
    if (!enc) {
        void* fn = nullptr;
        cudaDriverEntryPointQueryResult qr;
        cudaGetDriverEntryPoint("cuTensorMapEncodeTiled", &fn, cudaEnableDefault, &qr);
        enc = (EncodeFn)fn;
        cudaFuncSetAttribute(fused_kernel, cudaFuncAttributeMaxDynamicSharedMemorySize, SM_TOTAL);
        cudaGetSymbolAddress((void**)&gs, g_s);
        cudaGetSymbolAddress((void**)&ge, g_epoch);
        cudaGetSymbolAddress((void**)&gt, g_tab);
    }
    Hot p;
    Maps m;
    auto in = [&](int i) { return (const __nv_bfloat16*)d_in[i]; };
    p.u = in(0); p.are = in(1); p.aim = in(2); p.bre = in(3); p.bim = in(4); p.cre = in(5); p.cim = in(6);
    p.logdt = in(7); p.dskip = in(8); p.wr = in(10);
    p.out = (__nv_bfloat16*)d_out;
    p.zero = 0;
    p.s = gs;
    p.epoch = ge;
    p.tab = gt;
    const char *wg = (const char*)d_in[11], *wu = (const char*)d_in[12];
    p.swap = wu < wg;
    make_map(enc, &m.u, in(0), D_, L_, 0, ROW / 2, 32, CU_TENSOR_MAP_SWIZZLE_NONE);
    make_map(enc, &m.gu, wu < wg ? wu : wg, F_, D_, wu < wg ? wg - wu : wu - wg, 32, 64, CU_TENSOR_MAP_SWIZZLE_64B);
    make_map(enc, &m.wd, in(13), D_, F_, 64, 32, 64, CU_TENSOR_MAP_SWIZZLE_64B);
    fused_kernel<<<NCTA, NTHREADS, SM_TOTAL>>>(p, m);
}
```

```cpp
#include <cuda_runtime.h>
#include <cuda_bf16.h>
#include <cuda_fp16.h>
#include <cuda.h>
#include <stdint.h>
#include <stddef.h>
#include <type_traits>

#define SAFE_WAITS 0
#define X_E 0
#define OMASK 0xE1F
#define KDEBUG 0

namespace {

constexpr int L_ = 2048, D_ = 576, F_ = 4608;
constexpr int NMAIN = 128, NDOWN = 108, NCTA = 132, NTHREADS = 640;
constexpr int SPIN_LIMIT = 1 << 15;

constexpr int SM_SKIP = 448, SM_TAG = 452, SM_REC = 768;
constexpr int SM_STAT = 512;
constexpr int SM_GU = 1024, STAGE = 8192;
constexpr int SM_SLOT = 74752, SLOT = 24640;
constexpr int T_ADD = 2176, T_W4 = 2304, T_W8 = 2688, T_INV = 2976, T_PAD = 3056;
constexpr int T_X = 4416;
constexpr int T_B3 = 8768, T_B5 = 11856, T_B7 = 14944, T_B9 = 17024;
constexpr int T_F = 19104, T_S2 = 22368;
constexpr int SM_ROWS = 198016, ROW = 592;
constexpr int SM_XS = 216960, SM_PART = SM_XS;
constexpr int SM_WR = SM_XS + 2048, SM_ONES = SM_WR + 592, SM_DSK = 227328, SM_TAB = 227904;
constexpr int SM_TOTAL = 232448;
constexpr int KG_SCR = 3072;
constexpr int SV_CAND = 512, SV_XS = 896, SV_GU = 11264;
static_assert(SM_GU + 9 * STAGE == SM_SLOT && SM_SLOT + 5 * SLOT <= SM_ROWS && SM_ROWS + 32 * ROW == SM_XS && SM_ROWS % 128 == 0, "map");
static_assert(T_PAD + 5 * 272 == T_X && T_X + 16 * 272 == T_B3 && T_S2 + 8 * 272 <= SLOT && SLOT % 128 == 64, "map");

enum { B_X = 0, B_K = 2, B_T = 7, B_DONE = 12, B_FREE = 15, B_SEL, B_F = 18, B_W = 28, B_REC = 47, B_ROWS, B_ST, B_GO };
enum { N_KB = 1, N_X1 = 6, N_WG = 7 };

struct LaneTab { uint32_t w[6][32][4]; };
constexpr LaneTab make_tab() {
    LaneTab T{};
    for (int l = 0; l < 32; l++) {
        const int g = l >> 2, t = l & 3, mi = l >> 3, j = l & 7, h = mi & 1, hf = mi >> 1;
        auto xad = [](int c) { return T_X + 16 * (c + (c < 0 ? -1 : c >> 4)); };
        const int v[6][4] = {
            {T_X + 272 * j + 16 * (((mi + 1) >> 1) - 1), T_X + 272 * j + (mi ? 16 * (((mi + 1) >> 1) - 1) : -32), 4 * (7 + g - 2 * t), 4 * 36864 * g + 16 * t},
            {((j & 1) ? T_B5 : T_B3) + 16 * (7 + h - (j & 6) - hf), ((j & 1) ? T_B9 : T_B7 + 16) + 16 * (14 + h - (j & 6) - 8 * hf), T_F + 272 * hf + 32 * j + 16 * h, T_W4 + 8 * (g + t)},
            {(hf && j >= 4 ? T_F + 272 * (j - 4) : T_PAD) + 16 * h, (hf ? T_F + 272 * 4 : T_S2) + 272 * j + 16 * h, T_W8 + 4 * (g + t), g == 2 * t ? 0x5800 : g == 2 * t + 1 ? 0x58000000 : 0},
            {xad(l - 2) + 8, xad(l - 1), xad(l), l == 0 ? T_B3 : l == 1 ? T_B5 : T_B9},
            {512 * mi + 16 * j, T_X + (j & 1) * SLOT + 272 * (j >> 1) + 16 * mi, 512 * g + 16 * t, T_X + 272 * j + 16 * mi},
            {SM_ROWS + ROW * g + 16 * t, SM_STAT + 8 * g, 1152 * g + 16 * t, g}};
        for (int k = 0; k < 6; k++)
            for (int q = 0; q < 4; q++) T.w[k][l][q] = (uint32_t)v[k][q];
    }
    return T;
}
__device__ const __align__(128) LaneTab g_tab = make_tab();

struct Tune { int t_w, i1, n_w, i2, i3, skew, ws1, n_sv, ws2, t_x, d_x, d_x2, t_key, t_xs, nap, late, defer; };
#define TUNE 2300, 3000, 1, 650, 500, 60, 12, 18, 16, 5000, 300, 600, 4900, 7000, 100, 1, 3
constexpr Tune c_tune = {TUNE};
#define TN(x) std::integral_constant<int, c_tune.x>::value

struct Scratch {
    uint4 x[288 * 512];
    uint4 y[64 * 576 * 4];
    uint4 xs[16][8];
    uint32_t h[144 * 128];
    float part[44 * 12 * 128];
    uint2 key[L_];
    uint32_t cnt[40][32];
};
__device__ __align__(1024) Scratch g_s;
constexpr uint32_t G_X = offsetof(Scratch, x), G_Y = offsetof(Scratch, y), G_XS = offsetof(Scratch, xs), G_H = offsetof(Scratch, h), G_PART = offsetof(Scratch, part),
                   G_KEY = offsetof(Scratch, key), G_CNT = offsetof(Scratch, cnt);
__device__ uint32_t g_epoch[32] = {1};

struct Hot {
    const __nv_bfloat16 *are, *aim, *bre, *bim, *cre, *cim, *logdt, *u;
    const LaneTab* tab;
    char* s;
    uint32_t* epoch;
    const __nv_bfloat16 *wr, *dskip;
    __nv_bfloat16* out;
    uint32_t zero, swap;
};
struct alignas(128) Maps { CUtensorMap u, gu, wd; };
#define TS(i) do {} while (0)

__device__ __forceinline__ uint32_t smem_u32(const void* p) { return (uint32_t)__cvta_generic_to_shared(p); }
__device__ __forceinline__ void mbar_init(uint32_t b, int c) { asm volatile("mbarrier.init.shared::cta.b64 [%0], %1;" ::"r"(b), "r"(c) : "memory"); }
__device__ __forceinline__ void mbar_expect(uint32_t b, int bytes) { asm volatile("mbarrier.arrive.expect_tx.shared::cta.b64 _, [%0], %1;" ::"r"(b), "r"(bytes) : "memory"); }
__device__ __forceinline__ bool elect() { uint32_t d; asm volatile("{.reg .pred p; elect.sync _|p, 0xffffffff; selp.u32 %0,1,0,p;}" : "=r"(d)); return d; }
__device__ __forceinline__ void mbar_arrive(uint32_t b, uint32_t n) {
    asm volatile("{.reg .pred p; bar.warp.sync 0xffffffff; elect.sync _|p, 0xffffffff; @p mbarrier.arrive.shared::cta.b64 _, [%0], %1;}" ::"r"(b), "r"(n) : "memory");
}
__device__ __forceinline__ void mbar_arrive(uint32_t b) {
    asm volatile("{.reg .pred p; bar.warp.sync 0xffffffff; elect.sync _|p, 0xffffffff; @p mbarrier.arrive.shared::cta.b64 _, [%0];}" ::"r"(b) : "memory");
}
#define WAIT_LOOP(ins) "{\n.reg .pred p;\nLW:\n" ins " p, [%0], 0;\n@!p bra LW;\n}"
__device__ __forceinline__ void mbar_wait(uint32_t b) { asm volatile(WAIT_LOOP("bar.warp.sync 0xffffffff;\nmbarrier.try_wait.parity.shared::cta.b64")::"r"(b) : "memory"); }
__device__ __forceinline__ uint32_t mapa(uint32_t a, uint32_t rank) { uint32_t d; asm("mapa.shared::cluster.u32 %0, %1, %2;" : "=r"(d) : "r"(a), "r"(rank)); return d; }
__device__ __forceinline__ void tma3d(uint32_t dst, const CUtensorMap* m, int c0, int c1, uint32_t bar) {
    asm volatile("cp.async.bulk.tensor.3d.shared::cluster.global.mbarrier::complete_tx::bytes [%0], [%1, {%3, %4, %5}], [%2];" ::"r"(dst), "l"(m), "r"(bar), "r"(c0), "r"(c1), "r"(0) : "memory");
}
__device__ __forceinline__ void wgmma8(float (&d)[4], uint64_t da, uint64_t db) {
    asm volatile("wgmma.mma_async.sync.aligned.m64n8k16.f32.bf16.bf16 {%0,%1,%2,%3}, %4, %5, 1, 1, 1, 1, 0;"
                 : "+f"(d[0]), "+f"(d[1]), "+f"(d[2]), "+f"(d[3]) : "l"(da), "l"(db));
}
__device__ __forceinline__ void pf_tmap(const CUtensorMap* m) { asm volatile("prefetch.tensormap [%0];" ::"l"(m) : "memory"); }
__device__ __forceinline__ void bar_sync(int id, int n) { asm volatile("bar.sync %0, %1;" ::"r"(id), "r"(n) : "memory"); }
__device__ __forceinline__ void bar_arrive(int id, int n) { asm volatile("bar.arrive %0, %1;" ::"r"(id), "r"(n) : "memory"); }
__device__ __forceinline__ uint4 ld_rlx4(const void* p) { uint4 v; asm volatile("ld.relaxed.gpu.global.v4.u32 {%0,%1,%2,%3}, [%4];" : "=r"(v.x), "=r"(v.y), "=r"(v.z), "=r"(v.w) : "l"(p) : "memory"); return v; }
__device__ __forceinline__ uint32_t ld_rlx(const void* p) { uint32_t v; asm volatile("ld.relaxed.gpu.global.u32 %0, [%1];" : "=r"(v) : "l"(p) : "memory"); return v; }
__device__ __forceinline__ uint32_t ldg16(const void* p) { uint16_t v; asm volatile("ld.global.nc.u16 %0, [%1];" : "=h"(v) : "l"(p)); return v; }
__device__ __forceinline__ uint32_t ldg32(const void* p) { uint32_t v; asm volatile("ld.global.nc.u32 %0, [%1];" : "=r"(v) : "l"(p)); return v; }
__device__ __forceinline__ void bulk_g2s(uint32_t dst, const void* src, int bytes, uint32_t bar) {
    asm volatile("cp.async.bulk.shared::cluster.global.mbarrier::complete_tx::bytes [%0], [%1], %2, [%3];" ::"r"(dst), "l"(src), "r"(bytes), "r"(bar) : "memory");
}
__device__ __forceinline__ void stg128(void* p, uint32_t x, uint32_t y, uint32_t z, uint32_t w) { asm volatile("st.global.v4.u32 [%0], {%1,%2,%3,%4};" ::"l"(p), "r"(x), "r"(y), "r"(z), "r"(w) : "memory"); }
__device__ __forceinline__ void stg32(void* p, uint32_t v) { asm volatile("st.global.u32 [%0], %1;" ::"l"(p), "r"(v) : "memory"); }
__device__ __forceinline__ uint32_t lds32(uint32_t a) { uint32_t v; asm volatile("ld.shared.u32 %0, [%1];" : "=r"(v) : "r"(a) : "memory"); return v; }
__device__ __forceinline__ uint32_t lds16(uint32_t a) { uint16_t v; asm volatile("ld.shared.u16 %0, [%1];" : "=h"(v) : "r"(a) : "memory"); return v; }
__device__ __forceinline__ uint2 lds64(uint32_t a) { uint2 v; asm volatile("ld.shared.v2.u32 {%0,%1}, [%2];" : "=r"(v.x), "=r"(v.y) : "r"(a) : "memory"); return v; }
__device__ __forceinline__ uint4 lds128(uint32_t a) { uint4 v; asm volatile("ld.shared.v4.u32 {%0,%1,%2,%3}, [%4];" : "=r"(v.x), "=r"(v.y), "=r"(v.z), "=r"(v.w) : "r"(a) : "memory"); return v; }
__device__ __forceinline__ float4 lds128f(uint32_t a) { float4 v; asm volatile("ld.shared.v4.f32 {%0,%1,%2,%3}, [%4];" : "=f"(v.x), "=f"(v.y), "=f"(v.z), "=f"(v.w) : "r"(a) : "memory"); return v; }
__device__ __forceinline__ void sts32(uint32_t a, uint32_t v) { asm volatile("st.shared.u32 [%0], %1;" ::"r"(a), "r"(v) : "memory"); }
__device__ __forceinline__ void sts64(uint32_t a, uint32_t x, uint32_t y) { asm volatile("st.shared.v2.u32 [%0], {%1,%2};" ::"r"(a), "r"(x), "r"(y) : "memory"); }
__device__ __forceinline__ void sts128(uint32_t a, uint32_t x, uint32_t y, uint32_t z, uint32_t w) { asm volatile("st.shared.v4.u32 [%0], {%1,%2,%3,%4};" ::"r"(a), "r"(x), "r"(y), "r"(z), "r"(w) : "memory"); }
__device__ __forceinline__ void st_async(uint32_t a, float v, uint32_t bar) {
    asm volatile("st.async.shared::cluster.mbarrier::complete_tx::bytes.f32 [%0], %1, [%2];" ::"r"(a), "f"(v), "r"(bar) : "memory");
}
__device__ __forceinline__ void ldm4(uint32_t a, uint32_t (&r)[4]) {
    asm volatile("ldmatrix.sync.aligned.m8n8.x4.shared.b16 {%0,%1,%2,%3}, [%4];" : "=r"(r[0]), "=r"(r[1]), "=r"(r[2]), "=r"(r[3]) : "r"(a) : "memory");
}
__device__ __forceinline__ void ldm4t(uint32_t a, uint32_t (&r)[4]) {
    asm volatile("ldmatrix.sync.aligned.m8n8.x4.trans.shared.b16 {%0,%1,%2,%3}, [%4];" : "=r"(r[0]), "=r"(r[1]), "=r"(r[2]), "=r"(r[3]) : "r"(a) : "memory");
}
__device__ __forceinline__ void ldm2(uint32_t a, uint32_t& r0, uint32_t& r1) {
    asm volatile("ldmatrix.sync.aligned.m8n8.x2.shared.b16 {%0,%1}, [%2];" : "=r"(r0), "=r"(r1) : "r"(a) : "memory");
}
__device__ __forceinline__ void stm4(uint32_t a, uint32_t r0, uint32_t r1, uint32_t r2, uint32_t r3) {
    asm volatile("stmatrix.sync.aligned.m8n8.x4.shared.b16 [%0], {%1,%2,%3,%4};" ::"r"(a), "r"(r0), "r"(r1), "r"(r2), "r"(r3) : "memory");
}
__device__ __forceinline__ void stm4t(uint32_t a, uint32_t r0, uint32_t r1, uint32_t r2, uint32_t r3) {
    asm volatile("stmatrix.sync.aligned.m8n8.x4.trans.shared.b16 [%0], {%1,%2,%3,%4};" ::"r"(a), "r"(r0), "r"(r1), "r"(r2), "r"(r3) : "memory");
}
__device__ __forceinline__ void stm2t(uint32_t a, uint32_t r0, uint32_t r1) {
    asm volatile("stmatrix.sync.aligned.m8n8.x2.trans.shared.b16 [%0], {%1,%2};" ::"r"(a), "r"(r0), "r"(r1) : "memory");
}
__device__ __forceinline__ void mma_bf(float (&c)[4], const uint32_t (&a)[4], uint32_t b0, uint32_t b1) {
    asm volatile("mma.sync.aligned.m16n8k16.row.col.f32.bf16.bf16.f32 {%0,%1,%2,%3},{%4,%5,%6,%7},{%8,%9},{%0,%1,%2,%3};"
                 : "+f"(c[0]), "+f"(c[1]), "+f"(c[2]), "+f"(c[3]) : "r"(a[0]), "r"(a[1]), "r"(a[2]), "r"(a[3]), "r"(b0), "r"(b1));
}
__device__ __forceinline__ void mma_h(float (&c)[4], const uint32_t (&a)[4], uint32_t b0, uint32_t b1) {
    asm volatile("mma.sync.aligned.m16n8k16.row.col.f32.f16.f16.f32 {%0,%1,%2,%3},{%4,%5,%6,%7},{%8,%9},{%0,%1,%2,%3};"
                 : "+f"(c[0]), "+f"(c[1]), "+f"(c[2]), "+f"(c[3]) : "r"(a[0]), "r"(a[1]), "r"(a[2]), "r"(a[3]), "r"(b0), "r"(b1));
}
__device__ __forceinline__ void mma_hh(uint32_t (&d)[2], const uint32_t (&c)[2], const uint32_t (&a)[4], uint32_t b0, uint32_t b1) {
    asm volatile("mma.sync.aligned.m16n8k16.row.col.f16.f16.f16.f16 {%0,%1},{%2,%3,%4,%5},{%6,%7},{%8,%9};"
                 : "=r"(d[0]), "=r"(d[1]) : "r"(a[0]), "r"(a[1]), "r"(a[2]), "r"(a[3]), "r"(b0), "r"(b1), "r"(c[0]), "r"(c[1]));
}
__device__ __forceinline__ uint32_t pack_bf(float lo, float hi) { uint32_t r; asm("cvt.rn.bf16x2.f32 %0, %1, %2;" : "=r"(r) : "f"(hi), "f"(lo)); return r; }
__device__ __forceinline__ uint32_t pack_h(float lo, float hi) { uint32_t r; asm("cvt.rn.f16x2.f32 %0, %1, %2;" : "=r"(r) : "f"(hi), "f"(lo)); return r; }
__device__ __forceinline__ float bf_lo(uint32_t w) { return __uint_as_float(w << 16); }
__device__ __forceinline__ float bf_hi(uint32_t w) { return __uint_as_float(w & 0xFFFF0000u); }
__device__ __forceinline__ float bf_round(float x) { return __uint_as_float(pack_bf(0.f, x)); }
__device__ __forceinline__ uint32_t bsub(uint32_t a, uint32_t b) { uint32_t r; asm("sub.rn.bf16x2 %0, %1, %2;" : "=r"(r) : "r"(a), "r"(b)); return r; }
__device__ __forceinline__ uint32_t bmul(uint32_t a, uint32_t b) { uint32_t r; asm("mul.rn.bf16x2 %0, %1, %2;" : "=r"(r) : "r"(a), "r"(b)); return r; }
__device__ __forceinline__ uint32_t bfma(uint32_t a, uint32_t b, uint32_t c) { uint32_t r; asm("fma.rn.bf16x2 %0, %1, %2, %3;" : "=r"(r) : "r"(a), "r"(b), "r"(c)); return r; }
__device__ __forceinline__ uint32_t hadd(uint32_t a, uint32_t b) { uint32_t r; asm("add.rn.f16x2 %0, %1, %2;" : "=r"(r) : "r"(a), "r"(b)); return r; }
__device__ __forceinline__ uint32_t hmul(uint32_t a, uint32_t b) { uint32_t r; asm("mul.rn.f16x2 %0, %1, %2;" : "=r"(r) : "r"(a), "r"(b)); return r; }
__device__ __forceinline__ uint32_t hfma(uint32_t a, uint32_t b, uint32_t c) { uint32_t r; asm("fma.rn.f16x2 %0, %1, %2, %3;" : "=r"(r) : "r"(a), "r"(b), "r"(c)); return r; }
__device__ __forceinline__ uint32_t prmt(uint32_t a, uint32_t b, uint32_t s) { uint32_t r; asm("prmt.b32 %0, %1, %2, %3;" : "=r"(r) : "r"(a), "r"(b), "r"(s)); return r; }
__device__ __forceinline__ uint32_t settag(uint32_t v, uint32_t tag) { uint32_t r; asm("lop3.b32 %0, %1, %2, 1, 0xD8;" : "=r"(r) : "r"(v), "r"(tag)); return r; }
__device__ __forceinline__ float ex2f(float x) { float r; asm("ex2.approx.ftz.f32 %0, %1;" : "=f"(r) : "f"(x)); return r; }
__device__ __forceinline__ float rcpf(float x) { float r; asm("rcp.approx.ftz.f32 %0, %1;" : "=f"(r) : "f"(x)); return r; }
__device__ __forceinline__ float sqrt_ap(float x) { float r; asm("sqrt.approx.ftz.f32 %0, %1;" : "=f"(r) : "f"(x)); return r; }
__device__ __forceinline__ float silu_f(float x) { return x * rcpf(1.f + ex2f(-1.4426950408889634f * x)); }
__device__ __forceinline__ float silu_half(float h) { float r; asm("tanh.approx.f32 %0, %1;" : "=f"(r) : "f"(h)); return fmaf(h, r, h); }
__device__ __forceinline__ uint32_t clk32() { uint32_t c; asm volatile("mov.u32 %0, %%clock;" : "=r"(c)); return c; }
__device__ __forceinline__ void spin_until(uint32_t t) {
    asm volatile("{\n.reg .pred p;\n.reg .s32 c;\nLS:\nnanosleep.u32 20;\nmov.u32 c, %%clock;\nsub.s32 c, c, %0;\nsetp.lt.s32 p, c, 0;\n@p bra.uni LS;\n}" ::"r"(t) : "memory");
}
__device__ __forceinline__ void wait_flag(const void* p, uint32_t v) {
    asm volatile("{\n.reg .pred p;\n.reg .u32 c, n;\nmov.u32 n, 32768;\nLF:\nld.relaxed.gpu.global.u32 c, [%0];\nadd.u32 n, n, -1;\nsetp.ne.u32 p, n, 0;\n"
                 "setp.ne.and.u32 p, c, %1, p;\nvote.sync.any.pred p, p, 0xffffffff;\n@p bra.uni LF;\n}" ::"l"(p), "r"(v) : "memory");
}
__device__ __forceinline__ void stg128_if0(uint32_t c, void* p, uint32_t x, uint32_t y, uint32_t z, uint32_t w) {
    asm volatile("{.reg .pred q; setp.eq.u32 q, %5, 0; @q st.global.v4.u32 [%0], {%1,%2,%3,%4};}" ::"l"(p), "r"(x), "r"(y), "r"(z), "r"(w), "r"(c) : "memory");
}
__device__ __forceinline__ uint32_t movm(uint32_t v) { uint32_t r; asm volatile("movmatrix.sync.aligned.m8n8.trans.b16 %0, %1;" : "=r"(r) : "r"(v)); return r; }
__device__ __forceinline__ void cp16(uint32_t dst, const void* src) { asm volatile("cp.async.cg.shared.global [%0], [%1], 16;" ::"r"(dst), "l"(src) : "memory"); }
__device__ __forceinline__ void fence_async() { asm volatile("fence.proxy.async.shared::cta;" ::: "memory"); }
__device__ __forceinline__ uint32_t stale(uint32_t bad, uint32_t v, uint32_t tag) { uint32_t r; asm("lop3.b32 %0, %1, %2, %3, 0xF6;" : "=r"(r) : "r"(bad), "r"(v), "r"(tag)); return r; }
template <int M = 1>
__device__ __forceinline__ bool retry(uint32_t bad, int& it) {
    uint32_t r;
    asm volatile("{.reg .pred p; .reg .b32 b; and.b32 b, %2, %3; add.s32 %1, %1, -1; setp.ne.u32 p, b, 0; setp.gt.and.s32 p, %1, 0, p; vote.sync.any.pred p, p, 0xffffffff; selp.u32 %0, 1, 0, p;}"
                 : "=r"(r), "+r"(it) : "r"(bad), "n"(M));
    return r;
}
template <int N, int STEP>
__device__ __forceinline__ void poll(uint4 (&v)[N], const char* src, uint32_t tag) {
    int it = SPIN_LIMIT;
    bool again;
#pragma unroll 1
    do {
        uint32_t bad = 0;
#pragma unroll
        for (int k = 0; k < N; k++) v[k] = ld_rlx4(src + k * STEP);
#pragma unroll
        for (int k = 0; k < N; k++) bad = stale(bad, v[k].x, tag);
        again = retry(bad, it);
    } while (again);
}

struct cf { float x, y; };
__device__ __forceinline__ cf cmul(cf a, cf b) { return {a.x * b.x - a.y * b.y, a.x * b.y + a.y * b.x}; }
__device__ __forceinline__ cf csq(cf a) { return {a.x * a.x - a.y * a.y, (a.x + a.x) * a.y}; }
__device__ __forceinline__ cf cexp2(float zr2, float zi) {
    const float mag = ex2f(zr2);
    return {mag * __cosf(zi), mag * __sinf(zi)};
}
__device__ __forceinline__ __half2 as_h2(uint32_t v) { return *reinterpret_cast<__half2*>(&v); }
__device__ __forceinline__ uint32_t as_u32(__half2 v) { return *reinterpret_cast<uint32_t*>(&v); }
struct hm { uint32_t v, s; };
__device__ __forceinline__ hm mk_hm(cf a) { return {pack_h(a.x, a.y), pack_h(-a.y, a.x)}; }
__device__ __forceinline__ uint32_t operator*(uint32_t x, hm y) {
    const __half2 xx = as_h2(x);
    return as_u32(__hfma2(__high2half2(xx), as_h2(y.s), __hmul2(__low2half2(xx), as_h2(y.v))));
}
struct KParams { uint32_t are, aim, bre, bim, cre, cim, ldt; };

__device__ __forceinline__ void kgen(const KParams& kp, uint32_t scr, uint32_t l16) {
    const float dt = bf_round(ex2f(bf_lo(kp.ldt) * 1.4426950408889634f));
    cf w = cmul({bf_lo(kp.cre), bf_lo(kp.cim)}, {dt * bf_lo(kp.bre), dt * bf_lo(kp.bim)});
    const uint32_t eb = min(max(__reduce_max_sync(~0u, __float_as_uint(fmaxf(fabsf(w.x), fabsf(w.y)))) & 0x7F800000u, 0x00800000u), 0x7E000000u);
    const float sc = __uint_as_float(0x7F000000u - eb);
    w.x *= sc; w.y *= sc;
    const uint32_t k0 = pack_h(0.f, (float)__reduce_add_sync(~0u, __float2int_rn(w.x * 16777216.f)) * (1.f / 16777216.f));
    const float zr = dt * bf_lo(kp.are) * 1.4426950408889634f, zi = dt * bf_lo(kp.aim);
    const uint32_t st0 = l16 ^ ((l16 >> 3) & 48), st1 = st0 ^ 64, lb = (st0 & 112) + 8 * (l16 & 112), la = 8 * (l16 & 240) + ((l16 ^ (l16 >> 4)) & 112);
    auto st = [&](int row, uint32_t a, uint32_t b, uint32_t c, uint32_t e) { stm4(((row & 4) ? st1 : st0) + scr + row * 128, a, b, c, e); };
    uint32_t a[4][4], d[5][2];
    {
        const cf a16 = cexp2(16.f * zr, -16.f * zi), a32 = csq(a16), a64 = csq(a32);
        const hm m32 = mk_hm(a32), m64 = mk_hm(a64), m128 = mk_hm(csq(a64));
        const uint32_t p1 = pack_h(a16.x, a16.y), p2 = m32.v, p3 = p1 * m32, p5 = p1 * m64, p6 = p2 * m64, p7 = p3 * m64;
        st(0, 0x00003C00u, p1, p2, p3);
        st(4, m64.v, p5, p6, p7);
        st(8, m128.v, p1 * m128, p2 * m128, p3 * m128);
        st(12, m64.v * m128, p5 * m128, p6 * m128, p7 * m128);
        __syncwarp();
#pragma unroll
        for (int k = 0; k < 4; k++) ldm4((la ^ (k * 32)) + scr, a[k]);
    }
    auto tile = [&](int T, int row) {
        d[T][0] = d[T][1] = 0u;
#pragma unroll
        for (int k = 0; k < 2; k++) {
            uint32_t b[4];
            ldm4((lb ^ (k * 64)) + scr + row * 128, b);
            mma_hh(d[T], d[T], a[2 * k], b[0], b[1]);
            mma_hh(d[T], d[T], a[2 * k + 1], b[2], b[3]);
        }
    };
    const cf a1 = cexp2(zr, zi), a2 = csq(a1), a4 = csq(a2), u1 = cmul(w, a1);
    const hm m1 = mk_hm(a1), m2 = mk_hm(a2), m4 = mk_hm(a4), m8 = mk_hm(csq(a4));
    uint32_t v[17], e[9];
    v[1] = pack_h(u1.x, u1.y);
    v[2] = v[1] * m1;
    v[3] = v[1] * m2; v[4] = v[2] * m2;
#pragma unroll
    for (int i = 1; i <= 4; i++) v[4 + i] = v[i] * m4;
#pragma unroll
    for (int i = 1; i <= 8; i++) v[8 + i] = v[i] * m8;
    const cf a256 = cexp2(256.f * zr, 256.f * zi), a512 = csq(a256);
    const hm m256 = mk_hm(a256), m512 = mk_hm(a512), m1024 = mk_hm(csq(a512));
#pragma unroll
    for (int i = 1; i <= 8; i++) e[i] = v[2 * i] * m256;
    __syncwarp();
    st(0, v[1], v[2], v[5], v[6]);
    st(4, v[9], v[10], v[13], v[14]);
    st(8, v[3], v[4], v[7], v[8]);
    st(12, v[11], v[12], v[15], v[16]);
    st(16, e[1], e[2], e[3], e[4]);
    st(20, e[5], e[6], e[7], e[8]);
    __syncwarp();
    tile(0, 0); tile(1, 8); tile(2, 16);
    const uint32_t f8 = v[8] * m512, f16 = v[16] * m512, g8 = e[4] * m512, g16 = e[8] * m512;
    __syncwarp();
    st(0, v[4] * m512, f8, v[12] * m512, f16);
    st(4, e[2] * m512, g8, e[6] * m512, g16);
    st(8, v[8] * m1024, v[16] * m1024, e[4] * m1024, e[8] * m1024);
    st(12, f8 * m1024, f16 * m1024, g8 * m1024, g16 * m1024);
    __syncwarp();
    tile(3, 0); tile(4, 8);
    __syncwarp();
    sts128(scr + l16, d[2][0], d[2][1], k0, eb);
    sts128(scr + l16 + 512, d[0][0], d[1][0], d[0][1], d[1][1]);
    sts128(scr + l16 + 1024, d[3][0], d[3][1], d[4][0], d[4][1]);
}

__device__ __forceinline__ void ktables(uint32_t tab, int far, int lane) {
    uint4 c[4], v[4];
#pragma unroll
    for (int q = 0; q < 4; q++) { c[q] = lds128(tab + T_B3 + q * KG_SCR + lane * 16); v[q] = lds128(tab + T_B3 + q * KG_SCR + lane * 16 + 512 + 512 * far); }
    const uint32_t eb = max(max(c[0].w, c[1].w), max(c[2].w, c[3].w));
    const float rs = __uint_as_float(0x7F000000u - eb);
    uint32_t s[7] = {0u, 0u, 0u, 0u, 0u, 0u, 0u};
#pragma unroll
    for (int q = 0; q < 4; q++) {
        const float ff = __uint_as_float(c[q].w) * rs;
        const uint32_t f = pack_h(ff, ff);
        s[0] = hfma(v[q].x, f, s[0]); s[1] = hfma(v[q].y, f, s[1]); s[2] = hfma(v[q].z, f, s[2]); s[3] = hfma(v[q].w, f, s[3]);
        s[4] = hfma(c[q].x, f, s[4]); s[5] = hfma(c[q].y, f, s[5]); s[6] = hfma(c[q].z, f, s[6]);
    }
    if (far) {
        const int g = lane >> 2, t = lane & 3;
        const uint32_t a4 = tab + T_W4 + 4 * (14 + 2 * g + 32 * (t >> 1) + (t & 1)), a8 = tab + T_W8 + 4 * (7 + g + 16 * t);
        const uint32_t k1 = hmul(s[1], 0x20002000u);
        sts32(a4, hmul(s[0], 0x20002000u)); sts32(a4 + 64, k1);
        sts32(a8, hmul(s[2], 0x20002000u)); sts32(a8 + 32, hmul(s[3], 0x20002000u));
        if (lane == 31) sts64(tab + T_INV, prmt(eb + 0x00800000u, 0u, 0x3232), prmt(k1, 0u, 0x3232));
    } else {
        const uint32_t o = tab + 32 + lane * 16;
        const bool last = lane == 31;
        const uint32_t q0 = __shfl_sync(~0u, last ? s[6] : s[1], lane - 1), q1 = __shfl_sync(~0u, last ? s[1] : s[3], lane - 1);
        const uint32_t q2 = __shfl_sync(~0u, last ? s[3] : s[4], lane - 1), q3 = __shfl_sync(~0u, last ? s[4] : s[5], lane - 1);
        sts128(o, prmt(s[0], q0, 0x7610), prmt(s[0], 0u, 0x1032), prmt(s[1], s[0], 0x7610), prmt(s[1], 0u, 0x1032));
        sts128(o + 512, prmt(s[2], q1, 0x7610), prmt(s[2], 0u, 0x1032), prmt(s[3], s[2], 0x7610), prmt(s[3], 0u, 0x1032));
        sts128(o + 1024, prmt(q2, 0u, 0x3232), prmt(s[4], q2, 0x7610), prmt(s[4], 0u, 0x1032), prmt(s[4], 0u, 0x3232));
        const uint32_t aa = prmt(s[5], 0u, 0x3232);
        sts128(o + 1536, prmt(q3, 0u, 0x3232), prmt(s[5], q3, 0x7610), prmt(s[5], 0u, 0x1032), aa);
        if (last) { sts128(o + 1552, aa, aa, s[5] & 0xFFFF0000u, 0u); sts32(tab + 28, s[6] >> 16); }
    }
}

__device__ __forceinline__ void boxes(uint32_t slot, uint32_t r0, int n, uint4 lt, uint32_t l16) {
    uint32_t xi = slot + 544 * r0, o = slot + 512 * r0 + l16;
    sts128(lt.w + slot, 0u, 0u, 0u, 0u);
#pragma unroll 1
    do {
        const uint2 pv = lds64(lt.x + xi);
        const uint4 ow = lds128(lt.y + xi), nx = lds128(lt.z + xi);
        const uint32_t P[9] = {pv.x, pv.y, ow.x, ow.y, ow.z, ow.w, nx.x, nx.y, nx.z};
        uint32_t Q[8], S2[8], S4[6], b5[5];
#pragma unroll
        for (int k = 0; k < 8; k++) { Q[k] = prmt(P[k], P[k + 1], 0x5432); S2[k] = hadd(P[k], Q[k]); }
#pragma unroll
        for (int k = 0; k < 6; k++) S4[k] = hadd(S2[k], S2[k + 1]);
#pragma unroll
        for (int k = 0; k < 5; k++) b5[k] = hadd(S4[k + 1], P[k + 3]);
        const uint32_t b30 = hadd(Q[3], S2[4]);
        sts128(o + T_B3 + 16, b30, hadd(Q[4], S2[5]), hadd(Q[5], S2[6]), hadd(Q[6], S2[7]));
        sts128(o + T_B5 + 16, b5[0], b5[1], b5[2], b5[3]);
        if (n > 1) {
            sts128(o + T_B7 + 16, hadd(hadd(Q[0], S2[1]), S4[2]), hadd(hadd(Q[1], S2[2]), S4[3]), hadd(hadd(Q[2], S2[3]), S4[4]), hadd(b30, S4[5]));
            sts128(o + T_B9 + 16, hadd(S4[0], b5[1]), hadd(S4[1], b5[2]), hadd(S4[2], b5[3]), hadd(S4[3], b5[4]));
            sts128(lt.z + xi + (T_S2 - T_X), S2[4], S2[5], S2[6], S2[7]);
        }
        xi += 1088; o += 1024;
        asm volatile("" : "+r"(n));
    } while (--n);
}

#define CT(i)
__device__ __forceinline__ void conv_far(uint32_t slot, int nb, uint32_t fbar, bool all, uint32_t tb) {
    const uint4 lb = lds128(tb + 512);
    const uint32_t wa = lds32(tb + 1032) + slot;
    uint2 w4[10];
    uint32_t w8[8][2], f[12][2];
#pragma unroll
    for (int s = 0; s < 10; s++) w4[s] = lds64(lb.w + slot + 32 * s);
#pragma unroll
    for (int k = 0; k < 12; k++) f[k][0] = f[k][1] = 0u;
    auto it = [&](int i) {
        uint32_t q[3][4];
        ldm4t(lb.x + slot + 256 * i, q[0]);
        if (i >= 4) ldm4t(lb.y + slot + 256 * (i - 4), q[2]);
        ldm4t(lb.x + slot + 256 * i + 128, q[1]);
#pragma unroll
        for (int k = i; k < min(i + 5, 12); k++) mma_hh(f[k], f[k], q[0], w4[1 + 2 * (k - i)].x, w4[1 + 2 * (k - i)].y);
        if (i >= 4) {
#pragma unroll
            for (int k = i; k < 12; k++) mma_hh(f[k], f[k], q[2], w8[k - i][0], w8[k - i][1]);
        }
#pragma unroll
        for (int k = i; k < min(i + 5, 12); k++) mma_hh(f[k], f[k], q[1], w4[2 * (k - i)].x, w4[2 * (k - i)].y);
        if (i & 1) stm4t(lb.z + slot + 272 * (i - 1), f[i - 1][0], f[i - 1][1], f[i][0], f[i][1]);
    };
    bar_sync(nb, 64);
    CT(0);
#pragma unroll
    for (int i = 0; i < 4; i++) it(i);
#pragma unroll
    for (int s = 0; s < 8; s++) { w8[s][0] = lds32(wa + 32 * s); w8[s][1] = lds32(wa + 32 * s + 16); }
    mbar_arrive(fbar);
    CT(1);
    if (all) {
#pragma unroll
        for (int i = 4; i < 12; i++) it(i);
        mbar_arrive(fbar + 8);
    }
    CT(2);
}

__device__ __forceinline__ void conv_near(uint32_t slot, uint32_t fbar, int H, char* gs, uint32_t yoff, uint32_t ci, uint32_t tb, uint32_t tag, uint32_t z) {
    float acc[8][4];
    const uint4 la = lds128(tb);
    uint32_t xa = la.x + slot + 2176 * H, xb = la.y + slot + 2176 * H, ra = la.z + slot;
    uint32_t q[8][4], r[2][2];
    r[0][0] = lds32(ra + 32); r[0][1] = lds32(ra);
#pragma unroll
    for (int i = 7; i >= 0; i--) ldm4((i ? xa : xb) + 32 * i, q[i]);
    auto step = [&](int s) {
        r[~s & 1][0] = lds32(ra + 64 * s + 96); r[~s & 1][1] = lds32(ra + 64 * s + 64);
        mma_h(acc[7], q[(7 - s) & 7], r[s & 1][0], r[s & 1][1]);
        q[(7 - s) & 7][3] = q[(8 - s) & 7][0] | z;
        ldm2(s == 7 ? xb - 272 : xa - 48 - 32 * s - (s & 8) * 2, q[(7 - s) & 7][0], q[(7 - s) & 7][1]);
#pragma unroll
        for (int i = 6; i >= 0; i--) mma_h(acc[i], q[(i - s) & 7], r[s & 1][0], r[s & 1][1]);
        q[(7 - s) & 7][2] = q[(7 - s) & 7][1] | z;
    };
#pragma unroll
    for (int i = 0; i < 8; i++) acc[i][0] = acc[i][1] = acc[i][2] = acc[i][3] = 0.f;
    step(0);
    CT(0);
#pragma unroll 1
    for (int n = 0; n < 4; n++) {
#pragma unroll
        for (int s = 1; s <= 8; s++) step(s);
        xa -= 272; xb -= 272; ra += 512;
    }
    CT(1);
    const uint4 lc = lds128(tb + 1024);
    const uint2 ik = lds64(slot + T_INV);
    const uint32_t aa = (H ? lc.y : lc.x) + slot, b1 = lc.w, b0 = hmul(b1, ik.y), inv = ik.x;
    char* yo = gs + (la.w + yoff);
    mbar_wait(fbar + 8 * H);
    CT(2);
    asm volatile("{.reg .pred p; setp.eq.u32 p, %1, 0; @p red.relaxed.gpu.global.add.u32 [%0], 1;}" ::"l"(gs + G_CNT + (ci + la.w)), "r"(la.w) : "memory");
#pragma unroll
    for (int a = 0; a < 4; a++) {
#pragma unroll
        for (int i = 2 * a; i < 2 * a + 2; i++) {
            ldm4(aa + 32 * i, q[i]);
            mma_h(acc[i], q[i], b0, b1);
        }
        stg128(yo + G_Y + a * 36864, settag(bmul(pack_bf(acc[2 * a][0], acc[2 * a][1]), inv), tag), bmul(pack_bf(acc[2 * a][2], acc[2 * a][3]), inv),
               bmul(pack_bf(acc[2 * a + 1][0], acc[2 * a + 1][1]), inv), bmul(pack_bf(acc[2 * a + 1][2], acc[2 * a + 1][3]), inv));
    }
    CT(3);
}

#define LEAVE return
__global__ void __cluster_dims__(2, 1, 1) __launch_bounds__(NTHREADS, 1) fused_kernel(const Hot p, const __grid_constant__ Maps m) {
    extern __shared__ __align__(1024) char smem[];
    const uint32_t t0 = clk32();
    const uint32_t tid = threadIdx.x, lane = tid & 31, bid = blockIdx.x, r = bid & 1, rb = bid >> 1;
    uint32_t c5 = 288 * (bid >> 6) + 256 + (rb & 31), c0 = c5 + (rb & 31) - 192 - 64 * r;
    uint32_t S = smem_u32(smem), l16 = 16 * lane;
    asm volatile("" : "+r"(S), "+r"(l16), "+r"(c0), "+r"(c5));
    const uint32_t warp = __shfl_sync(~0u, tid >> 5, 0), sub = warp & 3, grp = warp >> 2;
    uint32_t tag;
    const uint32_t ns = (bid * 171) >> 11, kq = bid - 12 * ns;
    uint32_t w0 = SM_GU, xs = SM_XS, bar = S + B_W * 8, slice = bid;

    if (bid < NMAIN) {
        if (warp == 16) {
            if (elect()) {
                mbar_init(S + B_ROWS * 8, 1);
                asm volatile("mbarrier.expect_tx.relaxed.cta.shared::cta.b64 [%0], %1;" ::"r"(S + B_ROWS * 8), "n"(32 * ROW + 576) : "memory");
                tma3d(S + SM_ROWS, &m.u, 144 * r, 32 * rb, S + B_ROWS * 8);
                bulk_g2s(S + SM_WR, p.wr + 288 * r, 576, S + B_ROWS * 8);
                mbar_init(S + B_GO * 8, 8); mbar_init(S + B_ST * 8, 8);
                pf_tmap(&m.gu);
            }
            __syncthreads();
            if (elect()) {
                asm volatile("mbarrier.expect_tx.relaxed.cta.shared::cta.b64 [%0], 3648;" ::"r"(S + B_GO * 8) : "memory");
                asm volatile("mbarrier.expect_tx.relaxed.cta.shared::cta.b64 [%0], 3072;" ::"r"(S + (B_K + 4) * 8) : "memory");
                asm volatile("mbarrier.expect_tx.relaxed.cta.shared::cta.b64 [%0], 1024;" ::"r"(S + B_ST * 8) : "memory");
                asm volatile("fence.mbarrier_init.release.cluster;" ::: "memory");
            }
            __syncwarp();
            asm volatile("barrier.cluster.arrive.relaxed.aligned;" ::: "memory");
            tag = ld_rlx(p.epoch);
            sts32(S + SM_TAG, tag);
            if (r) *(uint2*)(p.s + G_KEY + (256 * rb + 8 * lane)) = make_uint2(~tag, 0u);
            mbar_arrive(S + B_ROWS * 8);
            TS(0);
            const CUtensorMap* mp = &m.gu;
            int col = 16 * bid, row = 0;
            uint32_t dst = S + SM_GU, tn = t0 + TN(t_w) + (bid & 15) * TN(skew);
            if (elect()) { bulk_g2s(S + SM_TAB, p.tab, 3072, S + B_GO * 8); bulk_g2s(S + SM_DSK, p.dskip + 288 * r, 576, S + B_GO * 8); }
#pragma unroll 1
            for (int s = 0; s < 15; s++) {
                spin_until(tn);
                tn += s < TN(n_w) ? TN(i1) : s < 9 ? TN(i2) : TN(i3);
                if (s == 9) {
                    if (bid >= NDOWN) break;
                    TS(2);
                    mbar_wait(S + B_FREE * 8);
                    col = 32 * ns; row = 384 * kq; mp = &m.wd; dst = S + SM_GU;
                }
                if (elect()) {
                    mbar_expect(bar, STAGE);
                    tma3d(dst, mp, col, row, bar);
                }
                dst += STAGE; row += 64; bar += 8;
            }
            TS(1);
            LEAVE;
        }

        const uint32_t gq = grp >> 2, bi = sub - gq, ck = bi + (r & gq) * 2;
        KParams kp;
        if (warp != 19) {
            const uint32_t ko = (gq ? c5 : c0 + 64 * (grp & 2) + (grp & 1)) * 128 + 32 * ck + lane;
            kp.are = ldg16(p.are + ko); kp.aim = ldg16(p.aim + ko); kp.bre = ldg16(p.bre + ko);
            kp.bim = ldg16(p.bim + ko); kp.cre = ldg16(p.cre + ko); kp.cim = ldg16(p.cim + ko);
            kp.ldt = ldg16(p.logdt + (ko >> 7));
        }
        if (grp & 2) {
            if (elect()) {
#pragma unroll
                for (int i = 0; i < 6; i++) mbar_init(S + 48 * (warp - 8) + 8 * i, warp < 11 ? 4 : 1);
            }
#pragma unroll 1
            for (uint32_t i = 16 * tid - 4096; i < T_X; i += 4096)
#pragma unroll
                for (int k = 0; k < 5; k++) sts128(S + SM_SLOT + k * SLOT + i, 0u, 0u, 0u, 0u);
            if (tid >= 476) sts128(S + SM_ONES + 16 * (tid - 476), 0x3F803F80u, 0x3F803F80u, 0x3F803F80u, 0x3F803F80u);
        }
        __syncthreads();
        asm volatile("barrier.cluster.arrive.relaxed.aligned;" ::: "memory");
        if (grp >= 2) {
            asm volatile("barrier.cluster.wait.aligned;" ::: "memory");
            if (!gq) {
                const uint32_t t = lane & 3, pa = S + SM_PART + 1024 * r + 128 * (warp - 8) + 4 * (lane & 28);
                const uint32_t ad = S + ((lane & 8) ? ((lane & 7) ? SM_WR : SM_ONES) : SM_ROWS + ROW * (8 * sub + (lane & 7))) + 288 * (grp & 1) + (lane & 16);
                float d[3][4];
#pragma unroll
                for (int i = 0; i < 3; i++) d[i][0] = d[i][1] = d[i][2] = d[i][3] = 0.f;
                mbar_wait(S + B_ROWS * 8);
                TS(0);
#pragma unroll
                for (int k = 0; k < 9; k++) {
                    uint32_t a[4];
                    ldm4(ad + 32 * k, a);
                    mma_bf(d[k % 3], a, a[0], a[2]);
                }
#pragma unroll
                for (int i = 0; i < 4; i++) d[0][i] += d[1][i] + d[2][i];
                const float s0 = __shfl_sync(~0u, d[0][2], t), s1 = __shfl_sync(~0u, d[0][3], t), w1 = __shfl_sync(~0u, d[0][2], t + 4);
                const bool odd = lane & 4;
                const float q = odd ? d[0][1] : d[0][0], s = odd ? s1 : s0, w = odd ? d[0][3] : w1;
                asm volatile("{.reg .pred p; setp.eq.u32 p, %0, %1;\n"
                             "@p st.async.shared::cluster.mbarrier::complete_tx::bytes.v4.f32 [%2], {%5,%6,%7,%8}, [%3];\n"
                             "@p st.shared.v4.f32 [%4], {%5,%6,%7,%8};}"
                             ::"r"(lane >> 3), "r"(t), "r"(pa ^ (1u << 24)), "r"((S ^ (1u << 24)) + B_ST * 8), "r"(pa), "f"(q), "f"(s), "f"(w), "f"(w1) : "memory");
                mbar_arrive(S + B_ST * 8);
                const uint32_t tg = lds32(S + SM_TAG + (l16 >> 9));
                uint32_t xa = S + SM_ROWS + 37 * l16 + 16 * (warp - 8), x[4];
                ldm4t(xa, x);
                mbar_wait(S + B_ST * 8);
                TS(1);
                float4 v[4];
#pragma unroll
                for (int i = 0; i < 4; i++) v[i] = lds128f(S + SM_PART + 512 * i + l16);
                const float mean = ((v[0].y + v[1].y) + (v[2].y + v[3].y)) * (1.f / 576.f);
                const float var = fmaxf(((v[0].x + v[1].x) + (v[2].x + v[3].x)) * (1.f / 576.f) - mean * mean, 0.f);
                const uint32_t ms = pack_bf(mean, sqrt_ap(bf_round(bf_round(var) + 1e-5f)));
                const float ri = 0.5f * rcpf(bf_hi(ms));
                sts64(S + SM_STAT + 8 * lane, __float_as_uint(ri), __float_as_uint(-bf_lo(ms) * ri));
                if (warp + r == 16) *(uint2*)(p.s + G_KEY + (256 * rb + 8 * lane)) = make_uint2(settag(__float_as_uint((v[0].z + v[1].z) + (v[2].z + v[3].z)), tg), ms);
                __syncwarp();
#pragma unroll
                for (int i = 0; i < 4; i++) v[i] = lds128f(S + SM_STAT + 64 * i + (l16 & 48));
                uint32_t xo = G_X + (144 * r + 4 * (warp - 8) + (lane >> 3)) * 8192 + 128 * rb + (l16 & 112);
#pragma unroll 1
                for (int b = grp & 1; b < 5; b++) {
                    float f[8];
#pragma unroll
                    for (int i = 0; i < 4; i++) { f[2 * i] = bf_lo(x[i]); f[2 * i + 1] = bf_hi(x[i]); }
                    xa += 128;
                    ldm4t(xa, x);
                    uint32_t o[4];
#pragma unroll
                    for (int i = 0; i < 4; i++) o[i] = pack_h(fmaf(f[2 * i], v[i].x, v[i].y), fmaf(f[2 * i + 1], v[i].z, v[i].w));
                    stg128(p.s + xo, settag(o[0], tg), o[1], o[2], o[3]);
                    xo += 32 * 8192;
                }
                mbar_arrive(S + B_GO * 8);
                TS(2);
            } else if (TN(late)) {
                mbar_wait(S + (TN(late) == 1 ? B_ST : TN(late) == 2 ? B_GO : B_K) * 8);
            }
        }
        if (warp != 19) {
            const uint32_t slot = S + SM_SLOT + grp * SLOT, scr = slot + T_B3 + ck * KG_SCR;
            kgen(kp, scr, l16);
            TS(4);
            if (gq) {
                fence_async();
                __syncwarp();
                if (elect())
                    asm volatile("cp.async.bulk.shared::cluster.shared::cta.mbarrier::complete_tx::bytes [%0], [%1], 1536, [%2];"
                                 ::"r"(scr ^ (1u << 24)), "r"(scr), "r"((S ^ (1u << 24)) + (B_K + 4) * 8) : "memory");
            }
            mbar_arrive(S + (B_K + grp) * 8, 1 + gq);
            if ((0x6F033u >> warp) & 1) {
                const uint32_t ts = grp - (bi >> 1);
                mbar_wait(S + (B_K + ts) * 8);
                ktables(S + SM_SLOT + ts * SLOT, bi & 1, lane);
                mbar_arrive(S + (B_T + ts) * 8, 2);
                TS(5);
            }
        }
        mbar_wait(S + B_GO * 8);
        tag = lds32(S + SM_TAG + (l16 >> 9));
        if (grp < 2) {
            const uint4 lr = lds128(S + SM_TAB + 2048 + l16);
            const char* src = p.s + G_X + (lr.x + (c0 + 128 * grp) * 4096 + 2048 * sub);
            const char* sr5 = p.s + G_X + (lr.z + (c5 >> 1) * 8192 + 64 * (c5 & 1) + 128 * sub);
            const uint32_t now = clk32();
            spin_until(now + max((int)(t0 + TN(t_x) - now), 0) + (grp ? TN(d_x2) : TN(d_x)));
            uint4 u[6];
            int it = SPIN_LIMIT;
            bool again;
            u[4].x = u[5].x = tag;
#pragma unroll 1
            do {
                uint32_t bad = 0;
#pragma unroll
                for (int k = 0; k < 6; k++)
                    if (k < 4 || grp) u[k] = ld_rlx4(k < 4 ? src + 128 * k : sr5 + 4096 * (k - 4));
#pragma unroll
                for (int k = 0; k < 6; k++) bad = stale(bad, u[k].x, tag);
                again = retry(bad, it);
            } while (again);
#pragma unroll
            for (int k = 0; k < 6; k++)
                if (k < 4 || grp)
                    stm4(k < 4 ? lr.y + S + SM_SLOT + 2 * SLOT * grp + 1088 * sub + 64 * k : lr.w + S + SM_SLOT + 4 * SLOT + 2176 * (k - 4) + 64 * sub, u[k].x, u[k].y, u[k].z, u[k].w);
            mbar_arrive(S + (B_X + grp) * 8);
            TS(6);
        }
        if (grp != 3) {
            if (warp != 19) {
                const uint32_t sl = __shfl_sync(~0u, warp == 8 ? 4 : gq ? 4 * bi : sub, 0), slot = S + SM_SLOT + sl * SLOT, fb = S + B_F * 8 + 16 * sl, tb = S + SM_TAB + l16;
                const bool far = warp > 8, all = sl + r < 5;
                const uint4 lt = lds128(tb + 1536);
                mbar_wait(S + (B_T + sl) * 8);
                mbar_wait(S + (B_X + (sl >= 2)) * 8);
                TS(9);
                if (grp) boxes(slot, far, all ? 3 : 1, lt, l16);
                TS(8);
                if (far) {
                    conv_far(slot, 1 + sl, fb, all, tb);
                    TS(7);
                } else {
                    if (grp) bar_arrive(1 + sl, 64);
                    const uint32_t ch = sl == 4 ? c5 : c0 + 64 * (sl & 2) + (sl & 1), H = grp && all;
                    conv_near(slot, fb, H, p.s, 32 * 36864 * H + 64 * ch, 8 * (ch & ~31u) + 128 * H, tb, tag, p.zero);
                    mbar_arrive(S + (B_DONE + grp) * 8);
                    TS(7);
                }
                if (!((OMASK >> warp) & 1)) LEAVE;
            } else {
                stg128(p.s + G_H + (512 * bid + l16), ~tag, ~tag, ~tag, ~tag);
#pragma unroll
                for (int i = 0; i < 4; i++) stg128(p.s + G_PART + 6144 * i + ((48 * ns + kq) * 512 + l16), ~tag, ~tag, ~tag, ~tag);
                __nanosleep(max((int)(t0 + TN(t_xs) - clk32()), 0) >> 1);
                uint4 rec[1];
                poll<1, 0>(rec, p.s + G_XS + (128 * (rb & 15) + (l16 & 112)), tag);
                sts128(S + SM_REC + (l16 & 112), rec[0].x, rec[0].y, rec[0].z, rec[0].w);
                uint32_t bit;
                asm("shl.b32 %0, 1, %1;" : "=r"(bit) : "r"(((rec[0].x >> 1) & 2047) - 32 * rb));
                sts32(S + SM_SKIP, __reduce_or_sync(~0u, bit));
                mbar_arrive(S + B_REC * 8);
                TS(7);
            }
            const uint32_t oc = 64 * __popc((uint32_t)OMASK << (31 - warp) << 1);
            const uint4 lo = lds128(S + SM_TAB + 2560 + l16);
            uint32_t cc[4][4], gt[4][4], xa = lo.x + S + oc, sa = lo.y + S;
            uint4 dk = lds128(S + SM_DSK + oc + (l16 & 48)), y[4];
            dk.x = bmul(dk.x, 0x40004000u); dk.y = bmul(dk.y, 0x40004000u); dk.z = bmul(dk.z, 0x40004000u); dk.w = bmul(dk.w, 0x40004000u);
            mbar_wait(S + B_REC * 8);
            const uint32_t skip = lds32(S + SM_SKIP) >> lo.w;
            char* oa = (char*)p.out + (lo.z + 36864 * rb + 576 * r + oc);
            const char* ya = p.s + G_Y + (lds32(S + SM_TAB + 2048 + l16) + bid * 18432 + 32 * oc);
            const char* fl = p.s + G_CNT + (2304 * r + 4 * oc + 2 * (bid & 64) + (l16 >> 9));
#pragma unroll
            for (int i = 0; i < 4; i++) {
                if (i == X_E) {
                    mbar_wait(S + (B_DONE + 1) * 8);
                    TS(10);
                    wait_flag(fl, 32 * tag);
                    TS(11);
#pragma unroll
                    for (int k = 0; k < 4; k++) y[k] = ld_rlx4(ya + 128 * k);
                }
                const uint4 x4 = lds128(xa + 8 * ROW * i);
                const uint2 st = lds64(sa + 64 * i);
                const uint32_t x[4] = {x4.x, x4.y, x4.z, x4.w}, d[4] = {dk.x, dk.y, dk.z, dk.w};
#pragma unroll
                for (int b = 0; b < 4; b++) {
                    const float h0 = fmaf(bf_lo(x[b]), __uint_as_float(st.x), __uint_as_float(st.y)), h1 = fmaf(bf_hi(x[b]), __uint_as_float(st.x), __uint_as_float(st.y));
                    gt[i][b] = pack_bf(silu_half(h0), silu_half(h1));
                    cc[i][b] = bfma(bmul(pack_bf(h0, h1), d[b]), gt[i][b], x[b]);
                    asm volatile("" : "+r"(gt[i][b]), "+r"(cc[i][b]));
                }
            }
            if (__any_sync(~0u, stale(stale(stale(y[0].x ^ tag, y[1].x, tag), y[2].x, tag), y[3].x, tag) & 1)) poll<4, 128>(y, ya, tag);
            TS(12);
#pragma unroll
            for (int i = 0; i < 4; i++) {
                uint32_t o[4];
#pragma unroll
                for (int b = 0; b < 4; b++) o[b] = bfma(movm(i == 0 ? y[b].x : i == 1 ? y[b].y : i == 2 ? y[b].z : y[b].w), gt[i][b], cc[i][b]);
                stg128_if0(skip & (1u << (8 * i)), oa + 9216 * i, o[0], o[1], o[2], o[3]);
            }
            TS(13);
            LEAVE;
        }
    } else {
        tag = ld_rlx(p.epoch + (lane & p.zero));
        if (elect()) {
#pragma unroll
            for (int i = 0; i < 3; i++) mbar_init(S + B_W * 8 + 24 * min(warp, 11) + 8 * i, 1);
            if (warp == 16) { mbar_init(S + B_FREE * 8, 4); mbar_init(S + B_SEL * 8, 4); pf_tmap(&m.gu); }
        }
        __syncthreads();
        if (warp >= 16) {
            if (warp == 16) {
                int col = 64 * bid - 6144, row = 0;
                uint32_t dst = S + SV_GU;
                spin_until(t0 + TN(t_w));
#pragma unroll 1
                for (int s = 0; s < 36; s++) {
                    if (s == TN(n_sv)) mbar_wait(S + B_SEL * 8);
                    const int w = s < TN(n_sv) ? TN(ws1) : TN(ws2);
                    if (s >= w) mbar_wait(S + (B_W + s - w) * 8);
                    if (s == 27) { mbar_wait(S + B_FREE * 8); fence_async(); dst = S + SV_GU; }
                    if (elect()) {
                        mbar_expect(S + (B_W + s) * 8, STAGE);
                        tma3d(dst, &m.gu, col, row, S + (B_W + s) * 8);
                    }
                    dst += STAGE; row += 64;
                    if (row == 576) { row = 0; col += 16; }
                }
            }
            TS(1);
            LEAVE;
        }
        char* xo = p.s + G_XS + (512 * (bid & 3) + l16);
        if (!warp) stg128(xo, ~tag, 0u, 0u, 0u);
        if (!sub) stg128(p.s + G_H + (512 * (4 * bid + grp - 384) + l16), ~tag, ~tag, ~tag, ~tag);
        if (tid == 0) sts32(S + SV_CAND, 0u);
        float sw = 0.f;
#pragma unroll
        for (int i = 0; i < 9; i++) { const uint32_t w = __ldg((const uint32_t*)p.wr + 32 * i + lane); sw += bf_lo(w) + bf_hi(w); }
#pragma unroll
        for (int o = 16; o > 0; o >>= 1) sw += __shfl_xor_sync(~0u, sw, o);
        spin_until(t0 + TN(t_key));
        uint4 v[2];
#pragma unroll 1
        for (int it = 0; it < SPIN_LIMIT; it++) {
            v[0] = ld_rlx4((const uint4*)(p.s + G_KEY) + tid); v[1] = ld_rlx4((const uint4*)(p.s + G_KEY) + tid + 512);
            if (!__any_sync(~0u, ((v[0].x ^ tag) | (v[0].z ^ tag) | (v[1].x ^ tag) | (v[1].z ^ tag)) & 1)) break;
        }
        TS(2);
        auto mk = [&](uint32_t dot, uint32_t ms, int row) {
            const uint32_t s = pack_bf(0.f, (__uint_as_float(dot) - bf_lo(ms) * sw) * rcpf(bf_hi(ms)));
            return (((s ^ (((int)s >> 31) | 0x80000000u)) >> 4) & 0x0FFFF000u) | (uint32_t)(4095 - row);
        };
        const uint32_t k[4] = {mk(v[0].x, v[0].y, 2 * tid), mk(v[0].z, v[0].w, 2 * tid + 1), mk(v[1].x, v[1].y, 2 * tid + 1024), mk(v[1].z, v[1].w, 2 * tid + 1025)};
        const uint32_t km[4] = {v[0].y, v[0].w, v[1].y, v[1].w};
        const uint32_t kx = max(max(k[0], k[1]), max(k[2], k[3]));
        const uint32_t wx = __reduce_max_sync(~0u, kx);
        sts32(S + SV_CAND + 16 + 4 * warp, wx);
        if (lane < 9) asm volatile("prefetch.global.L2 [%0];" ::"l"((const char*)p.u + ((4095 - (wx & 4095)) * 1152 + 8 * l16)));
        bar_sync(N_X1, 512);
        TS(5);
        const uint32_t mine = lds32(S + SV_CAND + 16 + 4 * (lane & 15));
        const uint4 o0 = lds128(S + SV_CAND + 16 + 2 * (lane & 16)), o1 = lds128(S + SV_CAND + 32 + 2 * (lane & 16));
        auto gt = [](uint32_t a, uint32_t b) { return (b - a) >> 31; };
        uint32_t rank = (gt(o0.x, mine) + gt(o0.y, mine) + gt(o0.z, mine)) + (gt(o0.w, mine) + gt(o1.x, mine) + gt(o1.y, mine)) + (gt(o1.z, mine) + gt(o1.w, mine));
        rank += __shfl_xor_sync(~0u, rank, 16);
        const uint32_t bound = __reduce_max_sync(~0u, rank == 7 ? mine : 0u);
        if (kx >= bound) {
            uint32_t pos;
            asm volatile("atom.shared.add.u32 %0, [%1], %2;" : "=r"(pos) : "r"(S + SV_CAND + (l16 >> 9)), "r"(32 - 8 * (gt(bound, k[0]) + gt(bound, k[1]) + (gt(bound, k[2]) + gt(bound, k[3])))) : "memory");
#pragma unroll
            for (int q = 0; q < 4; q++)
                if (k[q] >= bound) { sts64(S + SV_XS + pos, k[q], km[q]); pos += 8; }
        }
        bar_sync(N_X1, 512);
        TS(6);
        const int n8 = lds32(S + SV_CAND);
#pragma unroll 1
        for (int i = 8 * warp; i < n8; i += 128) {
            const uint2 c = lds64(S + SV_XS + i);
            const uint32_t row = 4095 - (c.x & 4095), k32 = (c.x << 4) & 0xFFFF0000u, sb = (k32 ^ ((~(int)k32 >> 31) | 0x80000000u)) & 0xFFFF0000u;
            if (lane < 9) asm volatile("prefetch.global.L2 [%0];" ::"l"((const char*)p.u + (row * 1152 + 8 * l16)));
            const uint32_t w = settag(pack_bf(0.f, rcpf(1.f + ex2f(-1.4426950408889634f * __uint_as_float(sb)))) | (row << 1), tag);
            const float ri = rcpf(bf_hi(c.y));
            rank = 0;
            int q = 0;
#pragma unroll 1
            do { rank += __popc(__ballot_sync(~0u, lds32(S + SV_XS + q + 8 * lane) > c.x && q + 8 * (int)lane < n8)); } while ((q += 256) < n8);
            if (rank < 8) sts128(S + SM_REC + 16 * rank, w, prmt(c.y, 0u, 0x1010), row * 1152, __float_as_uint(ri));
        }
        bar_sync(N_X1, 512);
        TS(3);
        if (!warp) { const uint4 rec = lds128(S + SM_REC + (l16 & 112)); stg128(xo, rec.x, rec.y, rec.z, rec.w); }
        TS(4);
        if (grp) mbar_wait(S + B_FREE * 8);
        w0 = SV_GU + (grp % 3) * 9 * STAGE; xs = SV_XS; bar = S + (B_W + 9 * grp) * 8; slice = 4 * bid + grp - 384;
    }

    {
    const uint32_t fi = tid & 127;
    const bool gate = (sub >> 1) == p.swap;
    char* ho = p.s + G_H + (512 * slice + 256 * (sub & 1) + 4 * lane);
    char* po = p.s + G_PART + (((4 * ns + sub) * 12 + kq) * 512 + 128 * (lane & 3) + (lane & 28));
    if (bid < NMAIN) mbar_wait(S + B_REC * 8);
    TS(7);
    float d[4];
    uint32_t fz;
#pragma unroll 1
    for (uint32_t ph = 0;; ph = 1) {
        if (bid < NMAIN || !grp) {
            uint4 v[5];
            uint32_t xd = S + SM_XS + 16 * fi + 2 * (fi & 120);
            if (ph) {
                const char* src = p.s + G_H + (6144 * kq + 16 * fi);
                int it = SPIN_LIMIT;
                uint32_t bad;
#pragma unroll 1
                do {
                    __nanosleep(TN(nap));
                    bad = 0;
#pragma unroll
                    for (int k = 0; k < 3; k++) v[k] = ld_rlx4(src + 2048 * k);
#pragma unroll
                    for (int k = 0; k < 3; k++) bad = stale(bad, v[k].x, tag);
                } while (retry(bad, it));
            } else {
                const uint4 rec = lds128(S + SM_REC + 2 * (fi & 56));
                const char* src = (const char*)p.u + (rec.z + (l16 & 112) + 64 * (sub & 2));
                xd = S + xs + 9 * (l16 & 112) + 2 * (fi & 56) + 576 * (sub & 2);
#pragma unroll
                for (int k = 0; k < 5; k++) {
                    if (k < 4 || sub < 2) v[k] = __ldg((const uint4*)(src + 256 * k));
                    v[k] = make_uint4(bsub(v[k].x, rec.y), bsub(v[k].y, rec.y), bsub(v[k].z, rec.y), bsub(v[k].w, rec.y));
                }
                sts128(xd + 3 * 2304, v[3].x, v[3].y, v[3].z, v[3].w);
                if (sub < 2) sts128(xd + 4 * 2304, v[4].x, v[4].y, v[4].z, v[4].w);
                if (!grp) mbar_arrive(S + B_SEL * 8);
            }
#pragma unroll
            for (int k = 0; k < 3; k++) sts128(xd + 2304 * k, v[k].x, v[k].y, v[k].z, v[k].w);
            if (ph) TS(9); else TS(8);
            fence_async();
            bar_sync(N_WG + grp, 128);
            if (ph && (TN(defer) & 2)) mbar_wait(S + (B_DONE + 1) * 8);
        }
        uint32_t da = (((S & 0xFFFF) + w0) >> 4) + (256 << 16), db = (((S & 0xFFFF) + xs) >> 4) + (9 << 16), n = 9 - 3 * ph, ok = 0;
        d[0] = d[1] = d[2] = d[3] = 0.f;
#pragma unroll 1
        do {
            if (bar == S + (B_W + 6) * 8 && grp) {
                asm volatile("wgmma.wait_group.sync.aligned 0;" ::: "memory");
                mbar_arrive(S + B_FREE * 8);
            }
            if (!ok) mbar_wait(bar);
            bar += 8;
            asm volatile("{.reg .pred p; mbarrier.test_wait.parity.shared::cta.b64 p, [%1], 0; selp.u32 %0,1,0,p;}" : "=r"(ok) : "r"(bar) : "memory");
            asm volatile("wgmma.fence.sync.aligned;" ::: "memory");
#pragma unroll
            for (int k = 0; k < 4; k++) wgmma8(d, (0x80000020ull << 32) + da + 64 * k, (uint64_t)db + 18 * k);
            asm volatile("wgmma.commit_group.sync.aligned;" ::: "memory");
            da += STAGE / 16; db += 72;
        } while (--n);
        if (ph) fz = ld_rlx(p.s + G_CNT + (128 * ((4 * ns + (kq >> 1)) & 62) + ((lds32(S + SM_REC + (fi & 112)) >> 4) & 128)));
        asm volatile("wgmma.wait_group.sync.aligned 0;" : "+f"(d[0]), "+f"(d[1]), "+f"(d[2]), "+f"(d[3])::"memory");
        if (ph) break;
        TS(10);
        const float r0 = __uint_as_float(lds32(S + SM_REC + 12 + 2 * (l16 & 48))), r1 = __uint_as_float(lds32(S + SM_REC + 28 + 2 * (l16 & 48)));
        const uint32_t ex = S + w0 + 6 * STAGE + 8 * (fi & 63), v0 = pack_bf(d[0] * r0, d[1] * r1), v1 = pack_bf(d[2] * r0, d[3] * r1);
        if (!gate) sts64(ex, v0, v1);
        bar_sync(N_WG + grp, 128);
        if (gate) {
            const uint2 u = lds64(ex);
            const uint32_t h0 = movm(bmul(pack_bf(silu_half(0.5f * bf_lo(v0)), silu_half(0.5f * bf_hi(v0))), u.x));
            const uint32_t h1 = movm(bmul(pack_bf(silu_half(0.5f * bf_lo(v1)), silu_half(0.5f * bf_hi(v1))), u.y));
            stg32(ho, settag(h0, (lane & 3) ? h0 : tag)); stg32(ho + 128, settag(h1, (lane & 3) ? h1 : tag));
        }
        if (!grp) mbar_arrive(S + B_FREE * 8);
        TS(11);
        if (bid >= NDOWN) LEAVE;
    }
#pragma unroll
    for (int i = 0; i < 4; i++) stg32(po + 64 * (i & 1) + 32 * (i >> 1), settag(__float_as_uint(d[i]), tag));
    TS(13);
    if (r && kq < 8) {
        const uint32_t tile = 4 * ns + (kq >> 1), cc = 16 * tile + (tid & 15);
        const uint4 rec = lds128(S + SM_REC + (fi & 112));
        const uint32_t row = (rec.x >> 1) & 2047, oi = (rec.z >> 1) + cc, xr = ldg16(p.u + oi), dk = ldg16(p.dskip + cc);
        const char* ya = p.s + G_Y + ((row >> 5) * 36864 + 64 * cc + 8 * (row & 6));
        const char* pa = p.s + G_PART + (tile * 6144 + 4 * fi);
        const char* fl = p.s + G_CNT + (128 * (tile & ~1u) + 128 * (row >> 10));
        uint32_t w[12];
        uint32_t f = fz;
        uint4 y;
        y.x = ~tag;
        int it = SPIN_LIMIT;
        bool again;
#pragma unroll 1
        do {
            if (f == 32 * tag && ((y.x ^ tag) & 1)) y = ld_rlx4(ya);
            f = ld_rlx(fl);
#pragma unroll
            for (int k = 0; k < 12; k++) w[k] = ld_rlx(pa + 512 * k);
            uint32_t bad = y.x ^ tag;
#pragma unroll
            for (int k = 0; k < 12; k++) bad = stale(bad, w[k], tag);
            again = retry(bad, it);
        } while (again);
        float s3[3];
#pragma unroll
        for (int k = 0; k < 3; k++) s3[k] = (__uint_as_float(w[4 * k]) + __uint_as_float(w[4 * k + 1])) + (__uint_as_float(w[4 * k + 2]) + __uint_as_float(w[4 * k + 3]));
        const float x = bf_lo(xr), xn = bf_round(bf_round(x - bf_lo(rec.y)) * __uint_as_float(rec.w));
        const bool hi = row & 16;
        const float sg = fmaf(xn, bf_lo(dk), bf_lo(prmt(hi ? y.z : y.x, hi ? y.w : y.y, 0x10 + 0x22 * (row & 1) + 0x44 * ((row >> 3) & 1))));
        const float up = bf_round(bf_round(s3[0] + s3[1] + s3[2]) * bf_hi(rec.x));
        p.out[oi] = __float2bfloat16(fmaf(sg, silu_half(0.5f * bf_round(xn + up)), x));
        if (bid + fi == 1) stg32(p.epoch, tag + 1);
        TS(14);
    }
    }
    LEAVE;
}

typedef CUresult (*EncodeFn)(CUtensorMap*, CUtensorMapDataType, cuuint32_t, void*, const cuuint64_t*, const cuuint64_t*, const cuuint32_t*,
                             const cuuint32_t*, CUtensorMapInterleave, CUtensorMapSwizzle, CUtensorMapL2promotion, CUtensorMapFloatOOBfill);

void make_map(EncodeFn enc, CUtensorMap* m, const void* base, uint64_t cols, uint64_t rows, uint64_t second, uint32_t bc, uint32_t br, CUtensorMapSwizzle sw) {
    cuuint64_t gd[3] = {cols / 2, rows, second ? 2u : 1u};
    cuuint64_t gs[2] = {cols * 2, second ? second : cols * 2 * rows};
    cuuint32_t bd[3] = {bc / 2, br, second ? 2u : 1u}, es[3] = {1, 1, 1};
    enc(m, CU_TENSOR_MAP_DATA_TYPE_UINT32, 3, const_cast<void*>(base), gd, gs, bd, es, CU_TENSOR_MAP_INTERLEAVE_NONE, sw,
        CU_TENSOR_MAP_L2_PROMOTION_L2_128B, CU_TENSOR_MAP_FLOAT_OOB_FILL_NONE);
}

}

extern "C" void kernel_launch(void* const* d_in, const int* in_sizes, int n_in, void* d_out, int out_size) {
    static EncodeFn enc = nullptr;
    static char* gs = nullptr;
    static LaneTab* gt = nullptr;
    static uint32_t* ge = nullptr;
    if (!enc) {
        void* fn = nullptr;
        cudaDriverEntryPointQueryResult qr;
        cudaGetDriverEntryPoint("cuTensorMapEncodeTiled", &fn, cudaEnableDefault, &qr);
        enc = (EncodeFn)fn;
        cudaFuncSetAttribute(fused_kernel, cudaFuncAttributeMaxDynamicSharedMemorySize, SM_TOTAL);
        cudaGetSymbolAddress((void**)&gs, g_s);
        cudaGetSymbolAddress((void**)&ge, g_epoch);
        cudaGetSymbolAddress((void**)&gt, g_tab);
    }
    Hot p;
    Maps m;
    auto in = [&](int i) { return (const __nv_bfloat16*)d_in[i]; };
    p.u = in(0); p.are = in(1); p.aim = in(2); p.bre = in(3); p.bim = in(4); p.cre = in(5); p.cim = in(6);
    p.logdt = in(7); p.dskip = in(8); p.wr = in(10);
    p.out = (__nv_bfloat16*)d_out;
    p.zero = 0;
    p.s = gs;
    p.epoch = ge;
    p.tab = gt;
    const char *wg = (const char*)d_in[11], *wu = (const char*)d_in[12];
    p.swap = wu < wg;
    make_map(enc, &m.u, in(0), D_, L_, 0, ROW / 2, 32, CU_TENSOR_MAP_SWIZZLE_NONE);
    make_map(enc, &m.gu, wu < wg ? wu : wg, F_, D_, wu < wg ? wg - wu : wu - wg, 32, 64, CU_TENSOR_MAP_SWIZZLE_64B);
    make_map(enc, &m.wd, in(13), D_, F_, 64, 32, 64, CU_TENSOR_MAP_SWIZZLE_64B);
    fused_kernel<<<NCTA, NTHREADS, SM_TOTAL>>>(p, m);
}
```

```cpp
#include <cuda_runtime.h>
#include <cuda_bf16.h>
#include <cuda_fp16.h>
#include <cuda.h>
#include <stdint.h>
#include <stddef.h>
#include <type_traits>

#define SAFE_WAITS 0
#define WP 19
#define WQ (35 - WP)
#define PNAP 100
#define XNAP 20
#define OMASK 0xE8F
#define KDEBUG 0

namespace {

constexpr int L_ = 2048, D_ = 576, F_ = 4608;
constexpr int NMAIN = 128, NDOWN = 108, NCTA = 132, NTHREADS = 640;
constexpr int SPIN_LIMIT = 1 << 15;

constexpr int SM_SKIP = 448, SM_TAG = 452, SM_TF = 456, SM_REC = 768;
constexpr int SM_STAT = 512;
constexpr int SM_GU = 1024, STAGE = 8192;
constexpr int SM_SLOT = 74752, SLOT = 24640;
constexpr int T_ADD = 2176, T_W4 = 2304, T_W8 = 2688, T_INV = 2976, T_PAD = 3056;
constexpr int T_X = 4416;
constexpr int T_B3 = 8768, T_B5 = 11856, T_B7 = 14944, T_B9 = 17024;
constexpr int T_F = 19104, T_S2 = 22368;
constexpr int SM_ROWS = 198016, ROW = 592;
constexpr int SM_XS = 216960, SM_PART = SM_XS;
constexpr int SM_WR = SM_XS + 2048, SM_ONES = SM_WR + 592, SM_DSK = 227328, SM_TAB = 227904;
constexpr int SM_TOTAL = 232448;
constexpr int KG_SCR = 3072;
constexpr int SV_CAND = 512, SV_XS = 896, SV_GU = 11264;
static_assert(SM_GU + 9 * STAGE == SM_SLOT && SM_SLOT + 5 * SLOT <= SM_ROWS && SM_ROWS + 32 * ROW == SM_XS && SM_ROWS % 128 == 0, "map");
static_assert(T_PAD + 5 * 272 == T_X && T_X + 16 * 272 == T_B3 && T_S2 + 8 * 272 <= SLOT && SLOT % 128 == 64, "map");

enum { B_X = 0, B_K = 2, B_T = 7, B_DONE = 12, B_FREE = 15, B_SEL, B_F = 18, B_W = 28, B_REC = 47, B_ROWS, B_ST, B_GO };
enum { N_KB = 1, N_X1 = 6, N_WG = 7 };

struct LaneTab { uint32_t w[6][32][4]; };
constexpr LaneTab make_tab() {
    LaneTab T{};
    for (int l = 0; l < 32; l++) {
        const int g = l >> 2, t = l & 3, mi = l >> 3, j = l & 7, h = mi & 1, hf = mi >> 1;
        auto xad = [](int c) { return T_X + 16 * (c + (c < 0 ? -1 : c >> 4)); };
        const int v[6][4] = {
            {T_X + 272 * j + 16 * (((mi + 1) >> 1) - 1), T_X + 272 * j + (mi ? 16 * (((mi + 1) >> 1) - 1) : -32), 4 * (7 + g - 2 * t), 4 * 36864 * g + 16 * t},
            {((j & 1) ? T_B5 : T_B3) + 16 * (7 + h - (j & 6) - hf), ((j & 1) ? T_B9 : T_B7 + 16) + 16 * (14 + h - (j & 6) - 8 * hf), T_F + 272 * hf + 32 * j + 16 * h, T_W4 + 8 * (g + t)},
            {(hf && j >= 4 ? T_F + 272 * (j - 4) : T_PAD) + 16 * h, (hf ? T_F + 272 * 4 : T_S2) + 272 * j + 16 * h, T_W8 + 4 * (g + t), g == 2 * t ? 0x5800 : g == 2 * t + 1 ? 0x58000000 : 0},
            {xad(l - 2) + 8, xad(l - 1), xad(l), l == 0 ? T_B3 : l == 1 ? T_B5 : T_B9},
            {512 * mi + 16 * j, T_X + (j & 1) * SLOT + 272 * (j >> 1) + 16 * mi, 512 * g + 16 * t, T_X + 272 * j + 16 * mi},
            {SM_ROWS + ROW * g + 16 * t, SM_STAT + 8 * g, 1152 * g + 16 * t, g}};
        for (int k = 0; k < 6; k++)
            for (int q = 0; q < 4; q++) T.w[k][l][q] = (uint32_t)v[k][q];
    }
    return T;
}
__device__ const __align__(128) LaneTab g_tab = make_tab();

struct Tune { int t_w, i1, n_w, i2, i3, skew, ws1, n_sv, ws2, t_x, d_x, d_x2, t_key, t_xs, nap, late, defer, win; };
#define TUNE 2300, 2500, 1, 620, 600, 40, 12, 22, 16, 5000, 300, 600, 4500, 6400, 100, 1, 3, 0
constexpr Tune c_tune = {TUNE};
#define TN(x) std::integral_constant<int, c_tune.x>::value

struct Scratch {
    uint4 x[288 * 512];
    uint4 y[64 * 576 * 4];
    uint4 xs[16][8];
    uint32_t h[144 * 128];
    float part[48 * 12 * 128];
    uint2 key[L_];
    uint32_t cnt[40][32];
};
__device__ __align__(1024) Scratch g_s;
constexpr uint32_t G_X = offsetof(Scratch, x), G_Y = offsetof(Scratch, y), G_XS = offsetof(Scratch, xs), G_H = offsetof(Scratch, h), G_PART = offsetof(Scratch, part),
                   G_KEY = offsetof(Scratch, key), G_CNT = offsetof(Scratch, cnt);
__device__ uint32_t g_epoch[32] = {1};

struct Hot {
    const __nv_bfloat16 *are, *aim, *bre, *bim, *cre, *cim, *logdt, *u;
    const LaneTab* tab;
    char* s;
    uint32_t* epoch;
    const __nv_bfloat16 *wr, *dskip;
    __nv_bfloat16* out;
    uint32_t zero, swap;
};
struct alignas(128) Maps { CUtensorMap u, gu, wd; };
#define TS(i) do {} while (0)

__device__ __forceinline__ uint32_t smem_u32(const void* p) { return (uint32_t)__cvta_generic_to_shared(p); }
__device__ __forceinline__ void mbar_init(uint32_t b, int c) { asm volatile("mbarrier.init.shared::cta.b64 [%0], %1;" ::"r"(b), "r"(c) : "memory"); }
__device__ __forceinline__ void mbar_expect(uint32_t b, int bytes) { asm volatile("mbarrier.arrive.expect_tx.shared::cta.b64 _, [%0], %1;" ::"r"(b), "r"(bytes) : "memory"); }
__device__ __forceinline__ bool elect() { uint32_t d; asm volatile("{.reg .pred p; elect.sync _|p, 0xffffffff; selp.u32 %0,1,0,p;}" : "=r"(d)); return d; }
__device__ __forceinline__ void mbar_arrive(uint32_t b, uint32_t n) {
    asm volatile("{.reg .pred p; bar.warp.sync 0xffffffff; elect.sync _|p, 0xffffffff; @p mbarrier.arrive.shared::cta.b64 _, [%0], %1;}" ::"r"(b), "r"(n) : "memory");
}
__device__ __forceinline__ void mbar_arrive(uint32_t b) {
    asm volatile("{.reg .pred p; bar.warp.sync 0xffffffff; elect.sync _|p, 0xffffffff; @p mbarrier.arrive.shared::cta.b64 _, [%0];}" ::"r"(b) : "memory");
}
#define WAIT_LOOP(ins) "{\n.reg .pred p;\nLW:\n" ins " p, [%0], 0;\n@!p bra LW;\n}"
__device__ __forceinline__ void mbar_wait(uint32_t b) { asm volatile(WAIT_LOOP("bar.warp.sync 0xffffffff;\nmbarrier.try_wait.parity.shared::cta.b64")::"r"(b) : "memory"); }
__device__ __forceinline__ uint32_t mapa(uint32_t a, uint32_t rank) { uint32_t d; asm("mapa.shared::cluster.u32 %0, %1, %2;" : "=r"(d) : "r"(a), "r"(rank)); return d; }
__device__ __forceinline__ void tma3d(uint32_t dst, const CUtensorMap* m, int c0, int c1, uint32_t bar) {
    asm volatile("cp.async.bulk.tensor.3d.shared::cluster.global.mbarrier::complete_tx::bytes [%0], [%1, {%3, %4, %5}], [%2];" ::"r"(dst), "l"(m), "r"(bar), "r"(c0), "r"(c1), "r"(0) : "memory");
}
__device__ __forceinline__ void wgmma8(float (&d)[4], uint64_t da, uint64_t db) {
    asm volatile("wgmma.mma_async.sync.aligned.m64n8k16.f32.bf16.bf16 {%0,%1,%2,%3}, %4, %5, 1, 1, 1, 1, 0;"
                 : "+f"(d[0]), "+f"(d[1]), "+f"(d[2]), "+f"(d[3]) : "l"(da), "l"(db));
}
__device__ __forceinline__ void pf_tmap(const CUtensorMap* m) { asm volatile("prefetch.tensormap [%0];" ::"l"(m) : "memory"); }
__device__ __forceinline__ void bar_sync(int id, int n) { asm volatile("bar.sync %0, %1;" ::"r"(id), "r"(n) : "memory"); }
__device__ __forceinline__ void bar_arrive(int id, int n) { asm volatile("bar.arrive %0, %1;" ::"r"(id), "r"(n) : "memory"); }
__device__ __forceinline__ uint4 ld_rlx4(const void* p) { uint4 v; asm volatile("ld.relaxed.gpu.global.v4.u32 {%0,%1,%2,%3}, [%4];" : "=r"(v.x), "=r"(v.y), "=r"(v.z), "=r"(v.w) : "l"(p) : "memory"); return v; }
__device__ __forceinline__ uint32_t ld_rlx(const void* p) { uint32_t v; asm volatile("ld.relaxed.gpu.global.u32 %0, [%1];" : "=r"(v) : "l"(p) : "memory"); return v; }
__device__ __forceinline__ uint32_t ldg16(const void* p) { uint16_t v; asm volatile("ld.global.nc.u16 %0, [%1];" : "=h"(v) : "l"(p)); return v; }
__device__ __forceinline__ uint32_t ldg32(const void* p) { uint32_t v; asm volatile("ld.global.nc.u32 %0, [%1];" : "=r"(v) : "l"(p)); return v; }
__device__ __forceinline__ void bulk_g2s(uint32_t dst, const void* src, int bytes, uint32_t bar) {
    asm volatile("cp.async.bulk.shared::cluster.global.mbarrier::complete_tx::bytes [%0], [%1], %2, [%3];" ::"r"(dst), "l"(src), "r"(bytes), "r"(bar) : "memory");
}
__device__ __forceinline__ void stg128(void* p, uint32_t x, uint32_t y, uint32_t z, uint32_t w) { asm volatile("st.global.v4.u32 [%0], {%1,%2,%3,%4};" ::"l"(p), "r"(x), "r"(y), "r"(z), "r"(w) : "memory"); }
__device__ __forceinline__ void stg32(void* p, uint32_t v) { asm volatile("st.global.u32 [%0], %1;" ::"l"(p), "r"(v) : "memory"); }
__device__ __forceinline__ uint32_t lds32(uint32_t a) { uint32_t v; asm volatile("ld.shared.u32 %0, [%1];" : "=r"(v) : "r"(a) : "memory"); return v; }
__device__ __forceinline__ uint32_t lds16(uint32_t a) { uint16_t v; asm volatile("ld.shared.u16 %0, [%1];" : "=h"(v) : "r"(a) : "memory"); return v; }
__device__ __forceinline__ uint2 lds64(uint32_t a) { uint2 v; asm volatile("ld.shared.v2.u32 {%0,%1}, [%2];" : "=r"(v.x), "=r"(v.y) : "r"(a) : "memory"); return v; }
__device__ __forceinline__ uint4 lds128(uint32_t a) { uint4 v; asm volatile("ld.shared.v4.u32 {%0,%1,%2,%3}, [%4];" : "=r"(v.x), "=r"(v.y), "=r"(v.z), "=r"(v.w) : "r"(a) : "memory"); return v; }
__device__ __forceinline__ float4 lds128f(uint32_t a) { float4 v; asm volatile("ld.shared.v4.f32 {%0,%1,%2,%3}, [%4];" : "=f"(v.x), "=f"(v.y), "=f"(v.z), "=f"(v.w) : "r"(a) : "memory"); return v; }
__device__ __forceinline__ void sts32(uint32_t a, uint32_t v) { asm volatile("st.shared.u32 [%0], %1;" ::"r"(a), "r"(v) : "memory"); }
__device__ __forceinline__ void sts64(uint32_t a, uint32_t x, uint32_t y) { asm volatile("st.shared.v2.u32 [%0], {%1,%2};" ::"r"(a), "r"(x), "r"(y) : "memory"); }
__device__ __forceinline__ void sts128(uint32_t a, uint32_t x, uint32_t y, uint32_t z, uint32_t w) { asm volatile("st.shared.v4.u32 [%0], {%1,%2,%3,%4};" ::"r"(a), "r"(x), "r"(y), "r"(z), "r"(w) : "memory"); }
__device__ __forceinline__ void st_async(uint32_t a, float v, uint32_t bar) {
    asm volatile("st.async.shared::cluster.mbarrier::complete_tx::bytes.f32 [%0], %1, [%2];" ::"r"(a), "f"(v), "r"(bar) : "memory");
}
__device__ __forceinline__ void ldm4(uint32_t a, uint32_t (&r)[4]) {
    asm volatile("ldmatrix.sync.aligned.m8n8.x4.shared.b16 {%0,%1,%2,%3}, [%4];" : "=r"(r[0]), "=r"(r[1]), "=r"(r[2]), "=r"(r[3]) : "r"(a) : "memory");
}
__device__ __forceinline__ void ldm4t(uint32_t a, uint32_t (&r)[4]) {
    asm volatile("ldmatrix.sync.aligned.m8n8.x4.trans.shared.b16 {%0,%1,%2,%3}, [%4];" : "=r"(r[0]), "=r"(r[1]), "=r"(r[2]), "=r"(r[3]) : "r"(a) : "memory");
}
__device__ __forceinline__ void ldm2(uint32_t a, uint32_t& r0, uint32_t& r1) {
    asm volatile("ldmatrix.sync.aligned.m8n8.x2.shared.b16 {%0,%1}, [%2];" : "=r"(r0), "=r"(r1) : "r"(a) : "memory");
}
__device__ __forceinline__ void stm4(uint32_t a, uint32_t r0, uint32_t r1, uint32_t r2, uint32_t r3) {
    asm volatile("stmatrix.sync.aligned.m8n8.x4.shared.b16 [%0], {%1,%2,%3,%4};" ::"r"(a), "r"(r0), "r"(r1), "r"(r2), "r"(r3) : "memory");
}
__device__ __forceinline__ void stm4t(uint32_t a, uint32_t r0, uint32_t r1, uint32_t r2, uint32_t r3) {
    asm volatile("stmatrix.sync.aligned.m8n8.x4.trans.shared.b16 [%0], {%1,%2,%3,%4};" ::"r"(a), "r"(r0), "r"(r1), "r"(r2), "r"(r3) : "memory");
}
__device__ __forceinline__ void stm2t(uint32_t a, uint32_t r0, uint32_t r1) {
    asm volatile("stmatrix.sync.aligned.m8n8.x2.trans.shared.b16 [%0], {%1,%2};" ::"r"(a), "r"(r0), "r"(r1) : "memory");
}
__device__ __forceinline__ void mma_bf(float (&c)[4], const uint32_t (&a)[4], uint32_t b0, uint32_t b1) {
    asm volatile("mma.sync.aligned.m16n8k16.row.col.f32.bf16.bf16.f32 {%0,%1,%2,%3},{%4,%5,%6,%7},{%8,%9},{%0,%1,%2,%3};"
                 : "+f"(c[0]), "+f"(c[1]), "+f"(c[2]), "+f"(c[3]) : "r"(a[0]), "r"(a[1]), "r"(a[2]), "r"(a[3]), "r"(b0), "r"(b1));
}
__device__ __forceinline__ void mma_h(float (&c)[4], const uint32_t (&a)[4], uint32_t b0, uint32_t b1) {
    asm volatile("mma.sync.aligned.m16n8k16.row.col.f32.f16.f16.f32 {%0,%1,%2,%3},{%4,%5,%6,%7},{%8,%9},{%0,%1,%2,%3};"
                 : "+f"(c[0]), "+f"(c[1]), "+f"(c[2]), "+f"(c[3]) : "r"(a[0]), "r"(a[1]), "r"(a[2]), "r"(a[3]), "r"(b0), "r"(b1));
}
__device__ __forceinline__ void mma_hh(uint32_t (&d)[2], const uint32_t (&c)[2], const uint32_t (&a)[4], uint32_t b0, uint32_t b1) {
    asm volatile("mma.sync.aligned.m16n8k16.row.col.f16.f16.f16.f16 {%0,%1},{%2,%3,%4,%5},{%6,%7},{%8,%9};"
                 : "=r"(d[0]), "=r"(d[1]) : "r"(a[0]), "r"(a[1]), "r"(a[2]), "r"(a[3]), "r"(b0), "r"(b1), "r"(c[0]), "r"(c[1]));
}
__device__ __forceinline__ uint32_t pack_bf(float lo, float hi) { uint32_t r; asm("cvt.rn.bf16x2.f32 %0, %1, %2;" : "=r"(r) : "f"(hi), "f"(lo)); return r; }
__device__ __forceinline__ uint32_t pack_h(float lo, float hi) { uint32_t r; asm("cvt.rn.f16x2.f32 %0, %1, %2;" : "=r"(r) : "f"(hi), "f"(lo)); return r; }
__device__ __forceinline__ float bf_lo(uint32_t w) { return __uint_as_float(w << 16); }
__device__ __forceinline__ float bf_hi(uint32_t w) { return __uint_as_float(w & 0xFFFF0000u); }
__device__ __forceinline__ float bf_round(float x) { return __uint_as_float(pack_bf(0.f, x)); }
__device__ __forceinline__ uint32_t bsub(uint32_t a, uint32_t b) { uint32_t r; asm("sub.rn.bf16x2 %0, %1, %2;" : "=r"(r) : "r"(a), "r"(b)); return r; }
__device__ __forceinline__ uint32_t bmul(uint32_t a, uint32_t b) { uint32_t r; asm("mul.rn.bf16x2 %0, %1, %2;" : "=r"(r) : "r"(a), "r"(b)); return r; }
__device__ __forceinline__ uint32_t bfma(uint32_t a, uint32_t b, uint32_t c) { uint32_t r; asm("fma.rn.bf16x2 %0, %1, %2, %3;" : "=r"(r) : "r"(a), "r"(b), "r"(c)); return r; }
__device__ __forceinline__ uint32_t hadd(uint32_t a, uint32_t b) { uint32_t r; asm("add.rn.f16x2 %0, %1, %2;" : "=r"(r) : "r"(a), "r"(b)); return r; }
__device__ __forceinline__ uint32_t hsub(uint32_t a, uint32_t b) { uint32_t r; asm volatile("sub.rn.f16x2 %0, %1, %2;" : "=r"(r) : "r"(a), "r"(b)); return r; }
__device__ __forceinline__ uint32_t hmul(uint32_t a, uint32_t b) { uint32_t r; asm("mul.rn.f16x2 %0, %1, %2;" : "=r"(r) : "r"(a), "r"(b)); return r; }
__device__ __forceinline__ uint32_t hfma(uint32_t a, uint32_t b, uint32_t c) { uint32_t r; asm("fma.rn.f16x2 %0, %1, %2, %3;" : "=r"(r) : "r"(a), "r"(b), "r"(c)); return r; }
__device__ __forceinline__ uint32_t prmt(uint32_t a, uint32_t b, uint32_t s) { uint32_t r; asm("prmt.b32 %0, %1, %2, %3;" : "=r"(r) : "r"(a), "r"(b), "r"(s)); return r; }
__device__ __forceinline__ uint32_t settag(uint32_t v, uint32_t tag) { uint32_t r; asm("lop3.b32 %0, %1, %2, 1, 0xD8;" : "=r"(r) : "r"(v), "r"(tag)); return r; }
__device__ __forceinline__ float ex2f(float x) { float r; asm("ex2.approx.ftz.f32 %0, %1;" : "=f"(r) : "f"(x)); return r; }
__device__ __forceinline__ float rcpf(float x) { float r; asm("rcp.approx.ftz.f32 %0, %1;" : "=f"(r) : "f"(x)); return r; }
__device__ __forceinline__ float sqrt_ap(float x) { float r; asm("sqrt.approx.ftz.f32 %0, %1;" : "=f"(r) : "f"(x)); return r; }
__device__ __forceinline__ float silu_f(float x) { return x * rcpf(1.f + ex2f(-1.4426950408889634f * x)); }
__device__ __forceinline__ float silu_half(float h) { float r; asm("tanh.approx.f32 %0, %1;" : "=f"(r) : "f"(h)); return fmaf(h, r, h); }
__device__ __forceinline__ uint32_t clk32() { uint32_t c; asm volatile("mov.u32 %0, %%clock;" : "=r"(c)); return c; }
template <int NAP = 20>
__device__ __forceinline__ void spin_until(uint32_t t) {
    asm volatile("{\n.reg .pred p;\n.reg .s32 c;\nLS:\nnanosleep.u32 %1;\nmov.u32 c, %%clock;\nsub.s32 c, c, %0;\nsetp.lt.s32 p, c, 0;\n@p bra.uni LS;\n}" ::"r"(t), "n"(NAP) : "memory");
}
__device__ __forceinline__ void wait_flag(const void* p, uint32_t v) {
    asm volatile("{\n.reg .pred p;\n.reg .u32 c, n;\nmov.u32 n, 32768;\nLF:\nld.relaxed.gpu.global.u32 c, [%0];\nadd.u32 n, n, -1;\nsetp.ne.u32 p, n, 0;\n"
                 "setp.ne.and.u32 p, c, %1, p;\nvote.sync.any.pred p, p, 0xffffffff;\n@p bra.uni LF;\n}" ::"l"(p), "r"(v) : "memory");
}
__device__ __forceinline__ void stg128_if0(uint32_t c, void* p, uint32_t x, uint32_t y, uint32_t z, uint32_t w) {
    asm volatile("{.reg .pred q; setp.eq.u32 q, %5, 0; @q st.global.v4.u32 [%0], {%1,%2,%3,%4};}" ::"l"(p), "r"(x), "r"(y), "r"(z), "r"(w), "r"(c) : "memory");
}
__device__ __forceinline__ uint32_t movm(uint32_t v) { uint32_t r; asm volatile("movmatrix.sync.aligned.m8n8.trans.b16 %0, %1;" : "=r"(r) : "r"(v)); return r; }
__device__ __forceinline__ void cp16(uint32_t dst, const void* src) { asm volatile("cp.async.cg.shared.global [%0], [%1], 16;" ::"r"(dst), "l"(src) : "memory"); }
__device__ __forceinline__ void fence_async() { asm volatile("fence.proxy.async.shared::cta;" ::: "memory"); }
__device__ __forceinline__ uint32_t stale(uint32_t bad, uint32_t v, uint32_t tag) { uint32_t r; asm("lop3.b32 %0, %1, %2, %3, 0xF6;" : "=r"(r) : "r"(bad), "r"(v), "r"(tag)); return r; }
template <int M = 1>
__device__ __forceinline__ bool retry(uint32_t bad, int& it) {
    uint32_t r;
    asm volatile("{.reg .pred p; .reg .b32 b; and.b32 b, %2, %3; add.s32 %1, %1, -1; setp.ne.u32 p, b, 0; setp.gt.and.s32 p, %1, 0, p; vote.sync.any.pred p, p, 0xffffffff; selp.u32 %0, 1, 0, p;}"
                 : "=r"(r), "+r"(it) : "r"(bad), "n"(M));
    return r;
}
template <int N, int STEP>
__device__ __forceinline__ void poll(uint4 (&v)[N], const char* src, uint32_t tag) {
    int it = SPIN_LIMIT;
    bool again;
#pragma unroll 1
    do {
        uint32_t bad = 0;
#pragma unroll
        for (int k = 0; k < N; k++) v[k] = ld_rlx4(src + k * STEP);
#pragma unroll
        for (int k = 0; k < N; k++) bad = stale(bad, v[k].x, tag);
        again = retry(bad, it);
    } while (again);
}

struct cf { float x, y; };
__device__ __forceinline__ cf cmul(cf a, cf b) { return {a.x * b.x - a.y * b.y, a.x * b.y + a.y * b.x}; }
__device__ __forceinline__ float mul2(float a, float b) { float r; asm("{.reg .f32 t; mul.ftz.f32 t, %1, %2; mul.ftz.f32 %0, t, 0f40000000;}" : "=f"(r) : "f"(a), "f"(b)); return r; }
__device__ __forceinline__ cf csq(cf a) { return {a.x * a.x - a.y * a.y, mul2(a.x, a.y)}; }
__device__ __forceinline__ cf cexp2(float zr2, float zi) {
    const float mag = ex2f(zr2);
    return {mag * __cosf(zi), mag * __sinf(zi)};
}
__device__ __forceinline__ __half2 as_h2(uint32_t v) { return *reinterpret_cast<__half2*>(&v); }
__device__ __forceinline__ uint32_t as_u32(__half2 v) { return *reinterpret_cast<uint32_t*>(&v); }
struct hm { uint32_t v, s; };
__device__ __forceinline__ hm mk_hm(cf a) { return {pack_h(a.x, a.y), pack_h(-a.y, a.x)}; }
__device__ __forceinline__ uint32_t operator*(uint32_t x, hm y) {
    const __half2 xx = as_h2(x);
    return as_u32(__hfma2(__high2half2(xx), as_h2(y.s), __hmul2(__low2half2(xx), as_h2(y.v))));
}
struct KParams { uint32_t are, aim, bre, bim, cre, cim, ldt; };

__device__ __forceinline__ void kgen(const KParams& kp, uint32_t scr, uint32_t l16) {
    const float dt = bf_round(ex2f(bf_lo(kp.ldt) * 1.4426950408889634f));
    cf w = cmul({bf_lo(kp.cre), bf_lo(kp.cim)}, {dt * bf_lo(kp.bre), dt * bf_lo(kp.bim)});
    const uint32_t eb = min(max(__reduce_max_sync(~0u, __float_as_uint(fmaxf(fabsf(w.x), fabsf(w.y)))) & 0x7F800000u, 0x00800000u), 0x7E000000u);
    const float sc = __uint_as_float(0x7F000000u - eb);
    w.x *= sc; w.y *= sc;
    const uint32_t k0 = pack_h(0.f, (float)__reduce_add_sync(~0u, __float2int_rn(w.x * 16777216.f)) * (1.f / 16777216.f));
    const float zr = dt * bf_lo(kp.are) * 1.4426950408889634f, zi = dt * bf_lo(kp.aim);
    const uint32_t st0 = l16 ^ ((l16 >> 3) & 48), st1 = st0 ^ 64, lb = (st0 & 112) + 8 * (l16 & 112), la = 8 * (l16 & 240) + ((l16 ^ (l16 >> 4)) & 112);
    auto st = [&](int row, uint32_t a, uint32_t b, uint32_t c, uint32_t e) { stm4(((row & 4) ? st1 : st0) + scr + row * 128, a, b, c, e); };
    uint32_t a[4][4], d[5][2];
    {
        const cf a16 = cexp2(16.f * zr, -16.f * zi), a32 = csq(a16), a64 = csq(a32);
        const hm m32 = mk_hm(a32), m64 = mk_hm(a64), m128 = mk_hm(csq(a64));
        uint32_t q[16];
        q[0] = 0x00003C00u; q[1] = pack_h(a16.x, a16.y); q[2] = m32.v; q[3] = q[1] * m32; q[4] = m64.v; q[8] = m128.v;
#pragma unroll
        for (int i = 1; i < 4; i++) q[4 + i] = q[i] * m64;
#pragma unroll
        for (int i = 1; i < 8; i++) { q[8 + i] = q[i] * m128; asm volatile("" : "+r"(q[8 + i])); }
#pragma unroll
        for (int i = 0; i < 16; i += 4) st(i, q[i], q[i + 1], q[i + 2], q[i + 3]);
        __syncwarp();
#pragma unroll
        for (int k = 0; k < 4; k++) ldm4((la ^ (k * 32)) + scr, a[k]);
    }
    auto tile = [&](int T, int row) {
        d[T][0] = d[T][1] = 0u;
#pragma unroll
        for (int k = 0; k < 2; k++) {
            uint32_t b[4];
            ldm4((lb ^ (k * 64)) + scr + row * 128, b);
            mma_hh(d[T], d[T], a[2 * k], b[0], b[1]);
            mma_hh(d[T], d[T], a[2 * k + 1], b[2], b[3]);
        }
    };
    const cf a1 = cexp2(zr, zi), a2 = csq(a1), a4 = csq(a2), u1 = cmul(w, a1);
    const hm m1 = mk_hm(a1), m2 = mk_hm(a2), m4 = mk_hm(a4), m8 = mk_hm(csq(a4));
    uint32_t v[17], e[9];
    v[1] = pack_h(u1.x, u1.y);
    v[2] = v[1] * m1;
    v[3] = v[1] * m2; v[4] = v[2] * m2;
#pragma unroll
    for (int i = 1; i <= 4; i++) v[4 + i] = v[i] * m4;
#pragma unroll
    for (int i = 1; i <= 8; i++) v[8 + i] = v[i] * m8;
    const cf a256 = cexp2(256.f * zr, 256.f * zi), a512 = csq(a256);
    const hm m256 = mk_hm(a256), m512 = mk_hm(a512), m1024 = mk_hm(csq(a512));
#pragma unroll
    for (int i = 1; i <= 8; i++) e[i] = v[2 * i] * m256;
    uint32_t f[16];
#pragma unroll
    for (int i = 0; i < 4; i++) { f[i] = v[4 * i + 4] * m512; f[4 + i] = e[2 * i + 2] * m512; }
#pragma unroll
    for (int i = 0; i < 2; i++) { f[8 + i] = v[8 * i + 8] * m1024; f[10 + i] = e[4 * i + 4] * m1024; f[12 + i] = f[2 * i + 1] * m1024; f[14 + i] = f[2 * i + 5] * m1024; }
#pragma unroll
    for (int i = 0; i < 16; i++) asm volatile("" : "+r"(f[i]));
#pragma unroll
    for (int i = 1; i <= 8; i++) asm volatile("" : "+r"(e[i]), "+r"(v[8 + i]));
    __syncwarp();
    st(0, v[1], v[2], v[5], v[6]);
    st(4, v[9], v[10], v[13], v[14]);
    st(8, v[3], v[4], v[7], v[8]);
    st(12, v[11], v[12], v[15], v[16]);
    st(16, e[1], e[2], e[3], e[4]);
    st(20, e[5], e[6], e[7], e[8]);
    __syncwarp();
    tile(0, 0); tile(1, 8); tile(2, 16);
    __syncwarp();
#pragma unroll
    for (int i = 0; i < 16; i += 4) st(i, f[i], f[i + 1], f[i + 2], f[i + 3]);
    __syncwarp();
    tile(3, 0); tile(4, 8);
    __syncwarp();
    sts128(scr + l16, d[2][0], d[2][1], k0, eb);
    sts128(scr + l16 + 512, d[0][0], d[0][1], d[1][0], d[1][1]);
    sts128(scr + l16 + 1024, d[3][0], d[3][1], d[4][0], d[4][1]);
}

__device__ __forceinline__ void ktables(uint32_t tab, int far, int lane) {
    uint4 c[4], v[4];
#pragma unroll
    for (int q = 0; q < 4; q++) { c[q] = lds128(tab + T_B3 + q * KG_SCR + lane * 16); v[q] = lds128(tab + T_B3 + q * KG_SCR + lane * 16 + 512 + 512 * far); }
    const uint32_t eb = max(max(c[0].w, c[1].w), max(c[2].w, c[3].w));
    const float rs = __uint_as_float(0x7F000000u - eb) * (1.f / 128.f);
    uint32_t s[7] = {0u, 0u, 0u, 0u, 0u, 0u, 0u};
#pragma unroll
    for (int q = 0; q < 4; q++) {
        const float ff = __uint_as_float(c[q].w) * rs;
        const uint32_t f = pack_h(ff, ff);
        s[0] = hfma(v[q].x, f, s[0]); s[1] = hfma(v[q].y, f, s[1]); s[2] = hfma(v[q].z, f, s[2]); s[3] = hfma(v[q].w, f, s[3]);
        s[4] = hfma(c[q].x, f, s[4]); s[5] = hfma(c[q].y, f, s[5]); s[6] = hfma(c[q].z, f, s[6]);
    }
    if (far) {
        const int g = lane >> 2, t = lane & 3;
        const uint32_t a4 = tab + T_W4 + 4 * (14 + 2 * g + 32 * (t >> 1) + (t & 1)), a8 = tab + T_W8 + 4 * (7 + g + 16 * t);
        sts32(a4, s[0]); sts32(a4 + 64, s[1]);
        sts32(a8, s[2]); sts32(a8 + 32, s[3]);
        if (lane == 31) sts64(tab + T_INV, prmt(eb + 0x00800000u, 0u, 0x3232), prmt(s[1], 0u, 0x3232));
    } else {
        { const uint32_t u = s[1]; s[1] = s[2]; s[2] = u; }
        const uint32_t o = tab + 32 + lane * 16;
        const bool last = lane == 31;
        const uint32_t q0 = __shfl_sync(~0u, last ? s[6] : s[1], lane - 1), q1 = __shfl_sync(~0u, last ? s[1] : s[3], lane - 1);
        const uint32_t q2 = __shfl_sync(~0u, last ? s[3] : s[4], lane - 1), q3 = __shfl_sync(~0u, last ? s[4] : s[5], lane - 1);
        sts128(o, prmt(s[0], q0, 0x7610), prmt(s[0], 0u, 0x1032), prmt(s[1], s[0], 0x7610), prmt(s[1], 0u, 0x1032));
        sts128(o + 512, prmt(s[2], q1, 0x7610), prmt(s[2], 0u, 0x1032), prmt(s[3], s[2], 0x7610), prmt(s[3], 0u, 0x1032));
        sts128(o + 1024, prmt(q2, 0u, 0x3232), prmt(s[4], q2, 0x7610), prmt(s[4], 0u, 0x1032), prmt(s[4], 0u, 0x3232));
        const uint32_t aa = prmt(s[5], 0u, 0x3232);
        sts128(o + 1536, prmt(q3, 0u, 0x3232), prmt(s[5], q3, 0x7610), prmt(s[5], 0u, 0x1032), aa);
        if (last) { sts128(o + 1552, aa, aa, s[5] & 0xFFFF0000u, 0u); sts32(tab + 28, s[6] >> 16); }
    }
}

__device__ __forceinline__ void boxes(uint32_t slot, uint32_t r0, int n, uint4 lt, uint32_t l16) {
    uint32_t xi = slot + 544 * r0, o = slot + 512 * r0 + l16;
    sts128(lt.w + slot, 0u, 0u, 0u, 0u);
#pragma unroll 1
    do {
        const uint2 pv = lds64(lt.x + xi);
        const uint4 ow = lds128(lt.y + xi), nx = lds128(lt.z + xi);
        const uint32_t P[9] = {pv.x, pv.y, ow.x, ow.y, ow.z, ow.w, nx.x, nx.y, nx.z};
        uint32_t Q[8], S2[8], S4[6], b5[5];
#pragma unroll
        for (int k = 0; k < 8; k++) { Q[k] = prmt(P[k], P[k + 1], 0x5432); S2[k] = hadd(P[k], Q[k]); }
#pragma unroll
        for (int k = 0; k < 6; k++) S4[k] = hadd(S2[k], S2[k + 1]);
#pragma unroll
        for (int k = 0; k < 5; k++) b5[k] = hadd(S4[k + 1], P[k + 3]);
        const uint32_t b30 = hadd(Q[3], S2[4]);
        sts128(o + T_B3 + 16, b30, hadd(Q[4], S2[5]), hadd(Q[5], S2[6]), hadd(Q[6], S2[7]));
        sts128(o + T_B5 + 16, b5[0], b5[1], b5[2], b5[3]);
        if (n > 1) {
            sts128(o + T_B7 + 16, hadd(hadd(Q[0], S2[1]), S4[2]), hadd(hadd(Q[1], S2[2]), S4[3]), hadd(hadd(Q[2], S2[3]), S4[4]), hadd(b30, S4[5]));
            sts128(o + T_B9 + 16, hadd(S4[0], b5[1]), hadd(S4[1], b5[2]), hadd(S4[2], b5[3]), hadd(S4[3], b5[4]));
            sts128(lt.z + xi + (T_S2 - T_X), S2[4], S2[5], S2[6], S2[7]);
        }
        xi += 1088; o += 1024;
        asm volatile("" : "+r"(n));
    } while (--n);
}

#define CT(i)
__device__ __forceinline__ void conv_far(uint32_t slot, int nb, uint32_t fbar, bool all, uint32_t tb) {
    const uint4 lb = lds128(tb + 512);
    const uint32_t wa = lds32(tb + 1032) + slot;
    uint2 w4[10];
    uint32_t w8[8][2], f[12][2];
#pragma unroll
    for (int s = 0; s < 10; s++) w4[s] = lds64(lb.w + slot + 32 * s);
#pragma unroll
    for (int k = 0; k < 12; k++) f[k][0] = f[k][1] = 0u;
    auto it = [&](int i) {
        uint32_t q[3][4];
        ldm4t(lb.x + slot + 256 * i, q[0]);
        if (i >= 4) ldm4t(lb.y + slot + 256 * (i - 4), q[2]);
        ldm4t(lb.x + slot + 256 * i + 128, q[1]);
#pragma unroll
        for (int k = i; k < min(i + 5, 12); k++) mma_hh(f[k], f[k], q[0], w4[1 + 2 * (k - i)].x, w4[1 + 2 * (k - i)].y);
        if (i >= 4) {
#pragma unroll
            for (int k = i; k < 12; k++) mma_hh(f[k], f[k], q[2], w8[k - i][0], w8[k - i][1]);
        }
#pragma unroll
        for (int k = i; k < min(i + 5, 12); k++) mma_hh(f[k], f[k], q[1], w4[2 * (k - i)].x, w4[2 * (k - i)].y);
        if (i & 1) stm4t(lb.z + slot + 272 * (i - 1), f[i - 1][0], f[i - 1][1], f[i][0], f[i][1]);
    };
    bar_sync(nb, 64);
    CT(0);
#pragma unroll
    for (int i = 0; i < 4; i++) it(i);
#pragma unroll
    for (int s = 0; s < 8; s++) { w8[s][0] = lds32(wa + 32 * s); w8[s][1] = lds32(wa + 32 * s + 16); }
    mbar_arrive(fbar);
    CT(1);
    if (all) {
#pragma unroll
        for (int i = 4; i < 12; i++) it(i);
        mbar_arrive(fbar + 8);
    }
    CT(2);
}

__device__ __forceinline__ void conv_near(uint32_t slot, uint32_t fbar, int H, char* gs, uint32_t yoff, uint32_t ci, uint32_t tb, uint32_t tga, uint32_t z) {
    uint32_t m[4][3][2], x[4][3][4], n[2][2], r[2][4];
    const uint2 la = lds64(tb);
    const uint32_t lr = lds32(tb + 8);
    uint32_t ux = slot + 2176 * H, ur = slot;
    auto load = [&](int w) {
        const int o = 64 * w + (w < 0 ? 16 * (w >> 2) : 0);
        ldm2(((w & 3) || w == 4 ? la.x : la.y) + ux + o, x[w & 3][0][0], x[w & 3][0][1]);
        ldm2(la.x + ux + o - ((w & 3) || w == 4 ? 32 : 48), n[w & 1][0], n[w & 1][1]);
    };
    auto build = [&](int w) {
        uint32_t(&q)[3][4] = x[w & 3];
        const uint32_t o0 = n[~w & 1][0], o1 = n[~w & 1][1], o2 = x[(w + 1) & 3][0][0];
        q[0][2] = q[0][1] | z; q[0][3] = o0 | z;
        q[1][0] = hsub(n[w & 1][0], q[0][0]); q[1][1] = hsub(n[w & 1][1], q[0][1]); q[1][2] = hsub(n[w & 1][1], q[0][2]); q[1][3] = hsub(q[0][0], o0);
        q[2][0] = hsub(o0, q[0][0]); q[2][1] = hsub(o1, q[0][1]); q[2][2] = hsub(o1, q[0][2]); q[2][3] = hsub(o2, o0);
    };
    auto step = [&](int j) {
#pragma unroll
        for (int k = 0; k < 4; k++) r[~j & 1][k] = lds32(lr + ur + 128 * (j + 1) + 32 * (k ^ 1));
        const uint32_t(&b)[4] = r[j & 1];
        const uint32_t s0 = hadd(b[0], b[2]), s1 = hadd(b[1], b[3]);
#pragma unroll
        for (int a = 3; a >= 0; a--) {
            const uint32_t(&q)[3][4] = x[(a - j) & 3];
            mma_hh(m[a][0], m[a][0], q[0], s0, s1); mma_hh(m[a][1], m[a][1], q[1], b[2], b[3]); mma_hh(m[a][2], m[a][2], q[2], b[0], b[1]);
            if (a == 3) load(-1 - j);
            if (a == 1) build(-1 - j);
        }
    };
#pragma unroll
    for (int i = 0; i < 12; i++) m[i / 3][i % 3][0] = m[i / 3][i % 3][1] = 0u;
#pragma unroll
    for (int k = 0; k < 4; k++) r[0][k] = lds32(lr + ur + 32 * (k ^ 1));
    load(4);
#pragma unroll
    for (int w = 3; w >= 0; w--) { load(w); build(w); }
    step(0);
    CT(0);
#pragma unroll 1
    for (int nb = 0; nb < 4; nb++) {
#pragma unroll
        for (int j = 1; j <= 4; j++) step(j);
        ux -= 272; ur += 512;
    }
    const uint32_t lw = lds32(tb + 12), tag = lds32(tga);
    uint32_t q[8][4];
    CT(1);
    const uint4 lc = lds128(tb + 1024);
    const uint2 ik = lds64(slot + T_INV);
    const uint32_t aa = (H ? lc.y : lc.x) + slot, b1 = lc.w, b0 = b1 | z, inv = ik.x;
    char* yo = gs + (lw + yoff);
    mbar_wait(fbar + 8 * H);
    CT(2);
    asm volatile("{.reg .pred p; setp.eq.u32 p, %1, 0; @p red.relaxed.gpu.global.add.u32 [%0], 1;}" ::"l"(gs + G_CNT + (ci + lw)), "r"(lw) : "memory");
#pragma unroll
    for (int a = 0; a < 4; a++) {
        float d[2][4] = {{0.f, 0.f, 0.f, 0.f}, {0.f, 0.f, 0.f, 0.f}};
#pragma unroll
        for (int i = 2 * a; i < 2 * a + 2; i++) {
            ldm4(aa + 32 * i, q[i]);
            q[i][0] = hfma(q[i][0], ik.y, m[a][0][0]); q[i][1] = hfma(q[i][1], ik.y, m[a][0][1]);
            q[i][2] = hadd(q[i][2], m[a][1 + (i & 1)][0]); q[i][3] = hadd(q[i][3], m[a][1 + (i & 1)][1]);
            mma_h(d[i & 1], q[i], b0, b1);
        }
        stg128(yo + G_Y + a * 36864, settag(bmul(pack_bf(d[0][0], d[0][1]), inv), tag), bmul(pack_bf(d[0][2], d[0][3]), inv),
               bmul(pack_bf(d[1][0], d[1][1]), inv), bmul(pack_bf(d[1][2], d[1][3]), inv));
    }
    CT(3);
}

#define LEAVE return
__global__ void __cluster_dims__(2, 1, 1) __launch_bounds__(NTHREADS, 1) fused_kernel(const __grid_constant__ Hot p, const __grid_constant__ Maps m) {
    extern __shared__ __align__(1024) char smem[];
    const uint32_t t0 = clk32();
    const uint32_t tid = threadIdx.x, lane = tid & 31, bid = blockIdx.x, r = bid & 1, rb = bid >> 1;
    uint32_t c5 = 288 * (bid >> 6) + 256 + (rb & 31), c0 = c5 + (rb & 31) - 192 - 64 * r;
    asm volatile("{.reg .pred q; setp.lt.u32 q, %1, 224; @q prefetch.global.L2 [%0];}"
                 ::"l"((const char*)(&p.are)[tid < 224 ? tid >> 5 : 0] + ((((tid & 4) ? c5 * 256 + 128 * r : c0 * 256 + 128 * (tid & 3))) >> (tid < 192 ? 0 : 7))), "r"(tid | (bid & 128) * 2 | (tid & 24) * 64));
    uint32_t S = smem_u32(smem), l16 = 16 * lane;
    asm volatile("" : "+r"(S), "+r"(l16), "+r"(c0), "+r"(c5));
    const uint32_t warp = __shfl_sync(~0u, tid >> 5, 0), sub = warp & 3, grp = warp >> 2;
    uint32_t tag;

    const uint32_t ns = (bid * 171) >> 11, kq = bid - 12 * ns;
    uint32_t w0 = SM_GU, xs = SM_XS, bar = S + B_W * 8, slice = bid;

    if (bid < NMAIN) {
        if (warp == WP) {
            if (elect()) {
                mbar_init(S + B_ROWS * 8, 1);
                asm volatile("mbarrier.expect_tx.relaxed.cta.shared::cta.b64 [%0], %1;" ::"r"(S + B_ROWS * 8), "n"(32 * ROW + 576) : "memory");
                tma3d(S + SM_ROWS, &m.u, 144 * r, 32 * rb, S + B_ROWS * 8);
                bulk_g2s(S + SM_WR, p.wr + 288 * r, 576, S + B_ROWS * 8);
                mbar_init(S + B_GO * 8, 8); mbar_init(S + B_ST * 8, 8);
                pf_tmap(&m.gu);
            }
            __syncthreads();
            if (elect()) {
                asm volatile("mbarrier.expect_tx.relaxed.cta.shared::cta.b64 [%0], 3648;" ::"r"(S + B_GO * 8) : "memory");
                asm volatile("mbarrier.expect_tx.relaxed.cta.shared::cta.b64 [%0], 3072;" ::"r"(S + (B_K + 4) * 8) : "memory");
                asm volatile("mbarrier.expect_tx.relaxed.cta.shared::cta.b64 [%0], 1024;" ::"r"(S + B_ST * 8) : "memory");
                asm volatile("fence.mbarrier_init.release.cluster;" ::: "memory");
            }
            __syncwarp();
            asm volatile("barrier.cluster.arrive.relaxed.aligned;" ::: "memory");
            tag = ld_rlx(p.epoch);
            sts32(S + SM_TAG, tag);
            if (r) *(uint2*)(p.s + G_KEY + (256 * rb + 8 * lane)) = make_uint2(~tag, 0u);
            mbar_arrive(S + B_ROWS * 8);
            TS(0);
            const CUtensorMap* mp = &m.gu;
            int col = 16 * bid, row = 0;
            uint32_t dst = S + SM_GU, tn = t0 + TN(t_w) + (bid & 15) * TN(skew);
            if (elect()) { bulk_g2s(S + SM_TAB, p.tab, 3072, S + B_GO * 8); bulk_g2s(S + SM_DSK, p.dskip + 288 * r, 576, S + B_GO * 8); }
#pragma unroll 1
            for (int s = 0; s < 15; s++) {
                spin_until<PNAP>(tn);
                if (TN(win) && s >= TN(win)) mbar_wait(bar - 8 * TN(win));
                tn += s < TN(n_w) ? TN(i1) : s < 9 ? TN(i2) : TN(i3);
                if (s == 9) {
                    if (bid >= NDOWN) break;
                    TS(2);
                    mbar_wait(S + B_FREE * 8);
                    col = 32 * ns; row = 384 * kq; mp = &m.wd; dst = S + SM_GU;
                }
                if (elect()) {
                    mbar_expect(bar, STAGE);
                    tma3d(dst, mp, col, row, bar);
                }
                dst += STAGE; row += 64; bar += 8;
            }
            TS(1);
            LEAVE;
        }

        const uint32_t gq = grp >> 2, bi = sub - gq, ck = bi + (r & gq) * 2;
        KParams kp;
        if (warp != WQ) {
            const uint32_t ko = (gq ? c5 : c0 + 64 * (grp & 2) + (grp & 1)) * 128 + 32 * ck + lane;
            kp.are = ldg16(p.are + ko); kp.aim = ldg16(p.aim + ko); kp.bre = ldg16(p.bre + ko);
            kp.bim = ldg16(p.bim + ko); kp.cre = ldg16(p.cre + ko); kp.cim = ldg16(p.cim + ko);
            kp.ldt = ldg16(p.logdt + (ko >> 7));
        }
        if (grp & 2) {
            if (elect()) {
#pragma unroll
                for (int i = 0; i < 6; i++) mbar_init(S + 48 * (warp - 8) + 8 * i, warp < 11 ? 4 : 1);
            }
#pragma unroll 1
            for (uint32_t i = 16 * tid - 4096; i < T_X; i += 4096)
#pragma unroll
                for (int k = 0; k < 5; k++) sts128(S + SM_SLOT + k * SLOT + i, 0u, 0u, 0u, 0u);
            if (tid >= 476) sts128(S + SM_ONES + 16 * (tid - 476), 0x3F803F80u, 0x3F803F80u, 0x3F803F80u, 0x3F803F80u);
        }
        __syncthreads();
        asm volatile("barrier.cluster.arrive.relaxed.aligned;" ::: "memory");
        if (grp >= 2) {
            asm volatile("barrier.cluster.wait.aligned;" ::: "memory");
            if (!gq) {
                const uint32_t t = lane & 3, pa = S + SM_PART + 1024 * r + 128 * (warp - 8) + 4 * (lane & 28);
                const uint32_t ad = S + ((lane & 8) ? ((lane & 7) ? SM_WR : SM_ONES) : SM_ROWS + ROW * (8 * sub + (lane & 7))) + 288 * (grp & 1) + (lane & 16);
                float d[3][4];
#pragma unroll
                for (int i = 0; i < 3; i++) d[i][0] = d[i][1] = d[i][2] = d[i][3] = 0.f;
                mbar_wait(S + B_ROWS * 8);
                TS(0);
#pragma unroll
                for (int k = 0; k < 9; k++) {
                    uint32_t a[4];
                    ldm4(ad + 32 * k, a);
                    mma_bf(d[k % 3], a, a[0], a[2]);
                }
#pragma unroll
                for (int i = 0; i < 4; i++) d[0][i] += d[1][i] + d[2][i];
                const float s0 = __shfl_sync(~0u, d[0][2], t), s1 = __shfl_sync(~0u, d[0][3], t), w1 = __shfl_sync(~0u, d[0][2], t + 4);
                const bool odd = lane & 4;
                const float q = odd ? d[0][1] : d[0][0], s = odd ? s1 : s0, w = odd ? d[0][3] : w1;
                asm volatile("{.reg .pred p; setp.eq.u32 p, %0, %1;\n"
                             "@p st.async.shared::cluster.mbarrier::complete_tx::bytes.v4.f32 [%2], {%5,%6,%7,%8}, [%3];\n"
                             "@p st.shared.v4.f32 [%4], {%5,%6,%7,%8};}"
                             ::"r"(lane >> 3), "r"(t), "r"(pa ^ (1u << 24)), "r"((S ^ (1u << 24)) + B_ST * 8), "r"(pa), "f"(q), "f"(s), "f"(w), "f"(w1) : "memory");
                mbar_arrive(S + B_ST * 8);
                const uint32_t tg = lds32(S + SM_TAG + (l16 >> 9));
                uint32_t xa = S + SM_ROWS + 37 * l16 + 16 * (warp - 8), x[4];
                ldm4t(xa, x);
                mbar_wait(S + B_ST * 8);
                TS(1);
                float4 v[4];
#pragma unroll
                for (int i = 0; i < 4; i++) v[i] = lds128f(S + SM_PART + 512 * i + l16);
                const float mean = ((v[0].y + v[1].y) + (v[2].y + v[3].y)) * (1.f / 576.f);
                const float var = fmaxf(((v[0].x + v[1].x) + (v[2].x + v[3].x)) * (1.f / 576.f) - mean * mean, 0.f);
                const uint32_t ms = pack_bf(mean, sqrt_ap(bf_round(bf_round(var) + 1e-5f)));
                const float ri = 0.5f * rcpf(bf_hi(ms));
                sts64(S + SM_STAT + 8 * lane, __float_as_uint(ri), __float_as_uint(-bf_lo(ms) * ri));
                if (warp + r == 16) *(uint2*)(p.s + G_KEY + (256 * rb + 8 * lane)) = make_uint2(settag(__float_as_uint((v[0].z + v[1].z) + (v[2].z + v[3].z)), tg), ms);
                __syncwarp();
#pragma unroll
                for (int i = 0; i < 4; i++) v[i] = lds128f(S + SM_STAT + 64 * i + (l16 & 48));
                uint32_t xo = G_X + (144 * r + 4 * (warp - 8) + (lane >> 3)) * 8192 + 128 * rb + (l16 & 112);
#pragma unroll 1
                for (int b = grp & 1; b < 5; b++) {
                    float f[8];
#pragma unroll
                    for (int i = 0; i < 4; i++) { f[2 * i] = bf_lo(x[i]); f[2 * i + 1] = bf_hi(x[i]); }
                    xa += 128;
                    ldm4t(xa, x);
                    uint32_t o[4];
#pragma unroll
                    for (int i = 0; i < 4; i++) o[i] = pack_h(fmaf(f[2 * i], v[i].x, v[i].y), fmaf(f[2 * i + 1], v[i].z, v[i].w));
                    stg128(p.s + xo, settag(o[0], tg), o[1], o[2], o[3]);
                    xo += 32 * 8192;
                }
                mbar_arrive(S + B_GO * 8);
                TS(2);
            } else if (TN(late)) {
                mbar_wait(S + (TN(late) == 1 ? B_ST : TN(late) == 2 ? B_GO : B_K) * 8);
            }
        }
        if (warp != WQ) {
            const uint32_t slot = S + SM_SLOT + grp * SLOT, scr = slot + T_B3 + ck * KG_SCR;
            kgen(kp, scr, l16);
            TS(4);
            if (gq) {
                fence_async();
                __syncwarp();
                if (elect())
                    asm volatile("cp.async.bulk.shared::cluster.shared::cta.mbarrier::complete_tx::bytes [%0], [%1], 1536, [%2];"
                                 ::"r"(scr ^ (1u << 24)), "r"(scr), "r"((S ^ (1u << 24)) + (B_K + 4) * 8) : "memory");
            }
            mbar_arrive(S + (B_K + grp) * 8, 1 + gq);
            if ((0x6F033u >> warp) & 1) {
                const uint32_t ts = grp - (bi >> 1);
                mbar_wait(S + (B_K + ts) * 8);
                ktables(S + SM_SLOT + ts * SLOT, bi & 1, lane);
                mbar_arrive(S + (B_T + ts) * 8, 2);
                TS(5);
            }
        }
        mbar_wait(S + B_GO * 8);
        tag = lds32(S + SM_TAG + (l16 >> 9));
        if (grp < 2) {
            const uint4 lr = lds128(S + SM_TAB + 2048 + l16);
            const char* src = p.s + G_X + (lr.x + (c0 + 128 * grp) * 4096 + 2048 * sub);
            const char* sr5 = p.s + G_X + (lr.z + (c5 >> 1) * 8192 + 64 * (c5 & 1) + 128 * sub);
            const uint32_t now = clk32();
            spin_until<XNAP>(now + max((int)(t0 + TN(t_x) - now), 0) + (grp ? TN(d_x2) : TN(d_x)));
            uint4 u[6];
            int it = SPIN_LIMIT;
            bool again;
            u[4].x = u[5].x = tag;
#pragma unroll 1
            do {
                uint32_t bad = 0;
#pragma unroll
                for (int k = 0; k < 6; k++)
                    if (k < 4 || grp) u[k] = ld_rlx4(k < 4 ? src + 128 * k : sr5 + 4096 * (k - 4));
#pragma unroll
                for (int k = 0; k < 6; k++) bad = stale(bad, u[k].x, tag);
                again = retry(bad, it);
            } while (again);
#pragma unroll
            for (int k = 0; k < 6; k++)
                if (k < 4 || grp)
                    stm4(k < 4 ? lr.y + S + SM_SLOT + 2 * SLOT * grp + 1088 * sub + 64 * k : lr.w + S + SM_SLOT + 4 * SLOT + 2176 * (k - 4) + 64 * sub, u[k].x, u[k].y, u[k].z, u[k].w);
            mbar_arrive(S + (B_X + grp) * 8);
            TS(6);
        }
        if (grp != 3) {
            if (warp != WQ) {

                const uint32_t sl = (uint32_t)((gq ? 0x420u : grp == 2 ? 0x3104u : 0x3102u) >> (4 * sub)) & 7,
                    slot = S + SM_SLOT + sl * SLOT, fb = S + B_F * 8 + 16 * sl, tb = S + SM_TAB + l16;
                const bool far = warp > 8, all = sl + r < 5;
                const uint4 lt = lds128(tb + 1536);
                mbar_wait(S + (B_T + sl) * 8);
                mbar_wait(S + (B_X + (sl >= 2)) * 8);
                TS(9);
                if (grp) boxes(slot, far, all ? 3 : 1, lt, l16);
                TS(8);
                if (far) {
                    conv_far(slot, 1 + sl, fb, all, tb);
                    TS(7);
                } else {
                    if (grp) bar_arrive(1 + sl, 64);
                    const uint32_t ch = sl == 4 ? c5 : c0 + 64 * (sl & 2) + (sl & 1), H = grp && all;
                    conv_near(slot, fb, H, p.s, 32 * 36864 * H + 64 * ch, 8 * (ch & ~31u) + 128 * H, tb, S + SM_TAG, p.zero);
                    mbar_arrive(S + (B_DONE + grp) * 8);
                    TS(7);
                }
                if (!((OMASK >> warp) & 1)) LEAVE;
                tag = lds32(S + SM_TAG + (l16 >> 9));
            } else {
                stg128(p.s + G_H + (512 * bid + l16), ~tag, ~tag, ~tag, ~tag);
#pragma unroll
                for (int i = 0; i < 4; i++) stg128(p.s + G_PART + 6144 * i + ((36 * ns + bid) * 512 + l16), ~tag, ~tag, ~tag, ~tag);
                __nanosleep(max((int)(t0 + TN(t_xs) - clk32()), 0) >> 1);
                uint4 rec[1];
                poll<1, 0>(rec, p.s + G_XS + (128 * (rb & 15) + (l16 & 112)), tag);
                sts128(S + SM_REC + (l16 & 112), rec[0].x, rec[0].y, rec[0].z, rec[0].w);
                uint32_t bit;
                asm("shl.b32 %0, 1, %1;" : "=r"(bit) : "r"(((rec[0].x >> 1) & 2047) - 32 * rb));
                sts32(S + SM_SKIP, __reduce_or_sync(~0u, bit));
                mbar_arrive(S + B_REC * 8);
                TS(7);
            }
            const uint32_t oc = 64 * __popc((uint32_t)OMASK << (31 - warp) << 1);
            const uint4 lo = lds128(S + SM_TAB + 2560 + l16);
            uint32_t cc[4][4], gt[4][4], xa = lo.x + S + oc, sa = lo.y + S;
            uint4 dk = lds128(S + SM_DSK + oc + (l16 & 48)), y[4];
            dk.x = bmul(dk.x, 0x40004000u); dk.y = bmul(dk.y, 0x40004000u); dk.z = bmul(dk.z, 0x40004000u); dk.w = bmul(dk.w, 0x40004000u);
            mbar_wait(S + B_REC * 8);
            const uint32_t skip = lds32(S + SM_SKIP) >> lo.w;
            char* oa = (char*)p.out + (lo.z + 36864 * rb + 576 * r + oc);
            const char* ya = p.s + G_Y + (lds32(S + SM_TAB + 2048 + l16) + bid * 18432 + 32 * oc);
            const char* fl = p.s + G_CNT + (2304 * r + 4 * oc + 2 * (bid & 64) + (l16 >> 9));
            auto fetch = [&]() {
                mbar_wait(S + (B_DONE + 1) * 8);
                TS(10);
                wait_flag(fl, 32 * tag);
                TS(11);
#pragma unroll
                for (int k = 0; k < 4; k++) y[k] = ld_rlx4(ya + 128 * k);
            };
            fetch();
#pragma unroll
            for (int i = 0; i < 4; i++) {
                const uint4 x4 = lds128(xa + 8 * ROW * i);
                const uint2 st = lds64(sa + 64 * i);
                const uint32_t x[4] = {x4.x, x4.y, x4.z, x4.w}, d[4] = {dk.x, dk.y, dk.z, dk.w};
#pragma unroll
                for (int b = 0; b < 4; b++) {
                    const float h0 = fmaf(bf_lo(x[b]), __uint_as_float(st.x), __uint_as_float(st.y)), h1 = fmaf(bf_hi(x[b]), __uint_as_float(st.x), __uint_as_float(st.y));
                    gt[i][b] = pack_bf(silu_half(h0), silu_half(h1));
                    cc[i][b] = bfma(bmul(pack_bf(h0, h1), d[b]), gt[i][b], x[b]);
                    asm volatile("" : "+r"(gt[i][b]), "+r"(cc[i][b]));
                }
            }
            if (__any_sync(~0u, stale(stale(stale(y[0].x ^ tag, y[1].x, tag), y[2].x, tag), y[3].x, tag) & 1)) poll<4, 128>(y, ya, tag);
            TS(12);
#pragma unroll
            for (int i = 0; i < 4; i++) {
                uint32_t o[4];
#pragma unroll
                for (int b = 0; b < 4; b++) o[b] = bfma(movm(i == 0 ? y[b].x : i == 1 ? y[b].y : i == 2 ? y[b].z : y[b].w), gt[i][b], cc[i][b]);
                stg128_if0(skip & (1u << (8 * i)), oa + 9216 * i, o[0], o[1], o[2], o[3]);
            }
            TS(13);
            LEAVE;
        }
    } else {
        tag = ld_rlx(p.epoch + (lane & p.zero));
        if (elect()) {
#pragma unroll
            for (int i = 0; i < 3; i++) mbar_init(S + B_W * 8 + 24 * min(warp, 11) + 8 * i, 1);
            if (warp == 16) { mbar_init(S + B_FREE * 8, 4); mbar_init(S + B_SEL * 8, 4); pf_tmap(&m.gu); }
        }
        __syncthreads();
        if (warp >= 16) {
            if (warp == 16) {
                int col = 64 * bid - 6144, row = 0;
                uint32_t dst = S + SV_GU;
                spin_until(t0 + TN(t_w));
#pragma unroll 1
                for (int s = 0; s < 36; s++) {
                    if (s == TN(n_sv)) mbar_wait(S + B_SEL * 8);
                    const int w = s < TN(n_sv) ? TN(ws1) : TN(ws2);
                    if (s >= w) mbar_wait(S + (B_W + s - w) * 8);
                    if (s == 27) { mbar_wait(S + B_FREE * 8); fence_async(); dst = S + SV_GU; }
                    if (elect()) {
                        mbar_expect(S + (B_W + s) * 8, STAGE);
                        tma3d(dst, &m.gu, col, row, S + (B_W + s) * 8);
                    }
                    dst += STAGE; row += 64;
                    if (row == 576) { row = 0; col += 16; }
                }
            }
            TS(1);
            LEAVE;
        }
        char* xo = p.s + G_XS + (512 * (bid & 3) + l16);
        if (!warp) stg128(xo, ~tag, 0u, 0u, 0u);
        if (!sub) stg128(p.s + G_H + (512 * (4 * bid + grp - 384) + l16), ~tag, ~tag, ~tag, ~tag);
        if (tid == 0) sts32(S + SV_CAND, 0u);
        float sw = 0.f;
#pragma unroll
        for (int i = 0; i < 9; i++) { const uint32_t w = __ldg((const uint32_t*)p.wr + 32 * i + lane); sw += bf_lo(w) + bf_hi(w); }
#pragma unroll
        for (int o = 16; o > 0; o >>= 1) sw += __shfl_xor_sync(~0u, sw, o);
        spin_until(t0 + TN(t_key));
        uint4 v[2];
#pragma unroll 1
        for (int it = 0; it < SPIN_LIMIT; it++) {
            v[0] = ld_rlx4((const uint4*)(p.s + G_KEY) + tid); v[1] = ld_rlx4((const uint4*)(p.s + G_KEY) + tid + 512);
            if (!__any_sync(~0u, ((v[0].x ^ tag) | (v[0].z ^ tag) | (v[1].x ^ tag) | (v[1].z ^ tag)) & 1)) break;
        }
        TS(2);
        auto mk = [&](uint32_t dot, uint32_t ms, int row) {
            const uint32_t s = pack_bf(0.f, (__uint_as_float(dot) - bf_lo(ms) * sw) * rcpf(bf_hi(ms)));
            return (((s ^ (((int)s >> 31) | 0x80000000u)) >> 4) & 0x0FFFF000u) | (uint32_t)(4095 - row);
        };
        const uint32_t k[4] = {mk(v[0].x, v[0].y, 2 * tid), mk(v[0].z, v[0].w, 2 * tid + 1), mk(v[1].x, v[1].y, 2 * tid + 1024), mk(v[1].z, v[1].w, 2 * tid + 1025)};
        const uint32_t km[4] = {v[0].y, v[0].w, v[1].y, v[1].w};
        const uint32_t kx = max(max(k[0], k[1]), max(k[2], k[3]));
        const uint32_t wx = __reduce_max_sync(~0u, kx);
        sts32(S + SV_CAND + 16 + 4 * warp, wx);
        if (lane < 9) asm volatile("prefetch.global.L2 [%0];" ::"l"((const char*)p.u + ((4095 - (wx & 4095)) * 1152 + 8 * l16)));
        bar_sync(N_X1, 512);
        TS(5);
        const uint32_t mine = lds32(S + SV_CAND + 16 + 4 * (lane & 15));
        const uint4 o0 = lds128(S + SV_CAND + 16 + 2 * (lane & 16)), o1 = lds128(S + SV_CAND + 32 + 2 * (lane & 16));
        auto gt = [](uint32_t a, uint32_t b) { return (b - a) >> 31; };
        uint32_t rank = (gt(o0.x, mine) + gt(o0.y, mine) + gt(o0.z, mine)) + (gt(o0.w, mine) + gt(o1.x, mine) + gt(o1.y, mine)) + (gt(o1.z, mine) + gt(o1.w, mine));
        rank += __shfl_xor_sync(~0u, rank, 16);
        const uint32_t bound = __reduce_max_sync(~0u, rank == 7 ? mine : 0u);
        if (kx >= bound) {
            uint32_t pos;
            asm volatile("atom.shared.add.u32 %0, [%1], %2;" : "=r"(pos) : "r"(S + SV_CAND + (l16 >> 9)), "r"(32 - 8 * (gt(bound, k[0]) + gt(bound, k[1]) + (gt(bound, k[2]) + gt(bound, k[3])))) : "memory");
#pragma unroll
            for (int q = 0; q < 4; q++)
                if (k[q] >= bound) { sts64(S + SV_XS + pos, k[q], km[q]); pos += 8; }
        }
        bar_sync(N_X1, 512);
        TS(6);
        const int n8 = lds32(S + SV_CAND);
#pragma unroll 1
        for (int i = 8 * warp; i < n8; i += 128) {
            const uint2 c = lds64(S + SV_XS + i);
            const uint32_t row = 4095 - (c.x & 4095), k32 = (c.x << 4) & 0xFFFF0000u, sb = (k32 ^ ((~(int)k32 >> 31) | 0x80000000u)) & 0xFFFF0000u;
            if (lane < 9) asm volatile("prefetch.global.L2 [%0];" ::"l"((const char*)p.u + (row * 1152 + 8 * l16)));
            const uint32_t w = settag(pack_bf(0.f, rcpf(1.f + ex2f(-1.4426950408889634f * __uint_as_float(sb)))) | (row << 1), tag);
            const float ri = rcpf(bf_hi(c.y));
            rank = 0;
            int q = 0;
#pragma unroll 1
            do { rank += __popc(__ballot_sync(~0u, lds32(S + SV_XS + q + 8 * lane) > c.x && q + 8 * (int)lane < n8)); } while ((q += 256) < n8);
            if (rank < 8) sts128(S + SM_REC + 16 * rank, w, prmt(c.y, 0u, 0x1010), row * 1152, __float_as_uint(ri));
        }
        bar_sync(N_X1, 512);
        TS(3);
        if (!warp) { const uint4 rec = lds128(S + SM_REC + (l16 & 112)); stg128(xo, rec.x, rec.y, rec.z, rec.w); }
        TS(4);
        if (grp) mbar_wait(S + B_FREE * 8);
        w0 = SV_GU + (grp % 3) * 9 * STAGE; xs = SV_XS; bar = S + (B_W + 9 * grp) * 8; slice = 4 * bid + grp - 384;
    }

    {
    const uint32_t fi = tid & 127;
    const bool gate = (sub >> 1) == p.swap;
    char* ho = p.s + G_H + (512 * slice + 256 * (sub & 1) + 4 * lane);
    char* po = p.s + G_PART + (((4 * ns + sub) * 12 + kq) * 512 + 128 * (lane & 3) + (lane & 28));
    const uint32_t ftok = fi & 112, fcol = fi & 15;
    const uint32_t tile = 4 * ns + (kq >> 1);
    const bool fin = r && kq < 8;
    if (bid < NMAIN) mbar_wait(S + B_REC * 8);
    TS(7);
    float d[4];
    uint32_t fz;
#pragma unroll 1
    for (uint32_t ph = 0;; ph = 1) {
        if (bid < NMAIN || !grp) {
            uint4 v[5];
            uint32_t xd = S + SM_XS + 16 * fi + 2 * (fi & 120);
            if (ph) {
                const char* src = p.s + G_H + (6144 * kq + 16 * fi);
                int it = SPIN_LIMIT;
                uint32_t bad;
#pragma unroll 1
                do {
                    __nanosleep(TN(nap));
                    bad = 0;
#pragma unroll
                    for (int k = 0; k < 3; k++) v[k] = ld_rlx4(src + 2048 * k);
#pragma unroll
                    for (int k = 0; k < 3; k++) bad = stale(bad, v[k].x, tag);
                } while (retry(bad, it));
            } else {
                const uint4 rec = lds128(S + SM_REC + 2 * (fi & 56));
                const char* src = (const char*)p.u + (rec.z + (l16 & 112) + 64 * (sub & 2));
                xd = S + xs + 9 * (l16 & 112) + 2 * (fi & 56) + 576 * (sub & 2);
#pragma unroll
                for (int k = 0; k < 5; k++) {
                    if (k < 4 || sub < 2) v[k] = __ldg((const uint4*)(src + 256 * k));
                    v[k] = make_uint4(bsub(v[k].x, rec.y), bsub(v[k].y, rec.y), bsub(v[k].z, rec.y), bsub(v[k].w, rec.y));
                }
                sts128(xd + 3 * 2304, v[3].x, v[3].y, v[3].z, v[3].w);
                if (sub < 2) sts128(xd + 4 * 2304, v[4].x, v[4].y, v[4].z, v[4].w);
                if (!grp) mbar_arrive(S + B_SEL * 8);
            }
#pragma unroll
            for (int k = 0; k < 3; k++) sts128(xd + 2304 * k, v[k].x, v[k].y, v[k].z, v[k].w);
            if (ph) TS(9); else TS(8);
            fence_async();
            bar_sync(N_WG + grp, 128);
            if (ph && (TN(defer) & 2)) mbar_wait(S + (B_DONE + 1) * 8);
        }
        uint32_t da = (((S & 0xFFFF) + w0) >> 4) + (256 << 16), db = (((S & 0xFFFF) + xs) >> 4) + (9 << 16), n = 9 - 3 * ph,
            ok = 0;
        d[0] = d[1] = d[2] = d[3] = 0.f;
#pragma unroll 1
        do {
            if (bar == S + (B_W + 6) * 8 && grp) {
                asm volatile("wgmma.wait_group.sync.aligned 0;" ::: "memory");
                mbar_arrive(S + B_FREE * 8);
            }
            if (!ok) mbar_wait(bar);
            bar += 8;
            asm volatile("{.reg .pred p; mbarrier.test_wait.parity.shared::cta.b64 p, [%1], 0; selp.u32 %0,1,0,p;}" : "=r"(ok) : "r"(bar) : "memory");
            asm volatile("wgmma.fence.sync.aligned;" ::: "memory");
#pragma unroll
            for (int k = 0; k < 4; k++) wgmma8(d, (0x80000020ull << 32) + da + 64 * k, (uint64_t)db + 18 * k);
            asm volatile("wgmma.commit_group.sync.aligned;" ::: "memory");
            da += STAGE / 16; db += 72;
        } while (--n);
        if (ph) fz = ld_rlx(p.s + G_CNT + (128 * min(tile & ~1u, 36u) + ((lds32(S + SM_REC + ftok) >> 4) & 128)));
        asm volatile("wgmma.wait_group.sync.aligned 0;" : "+f"(d[0]), "+f"(d[1]), "+f"(d[2]), "+f"(d[3])::"memory");
        if (ph) break;
        TS(10);
        const float r0 = __uint_as_float(lds32(S + SM_REC + 12 + 2 * (l16 & 48))), r1 = __uint_as_float(lds32(S + SM_REC + 28 + 2 * (l16 & 48)));
        const uint32_t ex = S + w0 + 6 * STAGE + 8 * (fi & 63), v0 = pack_bf(d[0] * r0, d[1] * r1), v1 = pack_bf(d[2] * r0, d[3] * r1);
        if (!gate) sts64(ex, v0, v1);
        bar_sync(N_WG + grp, 128);
        if (gate) {
            const uint2 u = lds64(ex);
            const uint32_t h0 = movm(bmul(pack_bf(silu_half(0.5f * bf_lo(v0)), silu_half(0.5f * bf_hi(v0))), u.x));
            const uint32_t h1 = movm(bmul(pack_bf(silu_half(0.5f * bf_lo(v1)), silu_half(0.5f * bf_hi(v1))), u.y));
            stg32(ho, settag(h0, (lane & 3) ? h0 : tag)); stg32(ho + 128, settag(h1, (lane & 3) ? h1 : tag));
        }
        if (!grp) mbar_arrive(S + B_FREE * 8);
        TS(11);
        if (bid >= NDOWN) LEAVE;
    }
#pragma unroll
    for (int i = 0; i < 4; i++) stg32(po + 64 * (i & 1) + 32 * (i >> 1), settag(__float_as_uint(d[i]), tag));
    TS(13);
    if (fin) {
        const uint32_t cc = 16 * tile + fcol;
        const uint4 rec = lds128(S + SM_REC + ftok);
        const uint32_t row = (rec.x >> 1) & 2047, oi = (rec.z >> 1) + cc, xr = ldg16(p.u + oi), dk = ldg16(p.dskip + cc);
        const char* ya = p.s + G_Y + ((row >> 5) * 36864 + 64 * cc + 8 * (row & 6));
        const char* pa = p.s + G_PART + (tile * 6144 + 4 * fi);
        const char* fl = p.s + G_CNT + (128 * (tile & ~1u) + 128 * (row >> 10));
        uint32_t w[12];
        uint32_t f = fz;
        uint4 y;
        y.x = ~tag;
        int it = SPIN_LIMIT;
        bool again;
#pragma unroll 1
        do {
            if (f == 32 * tag && ((y.x ^ tag) & 1)) y = ld_rlx4(ya);
            f = ld_rlx(fl);
#pragma unroll
            for (int k = 0; k < 12; k++) w[k] = ld_rlx(pa + 512 * k);
            uint32_t bad = y.x ^ tag;
#pragma unroll
            for (int k = 0; k < 12; k++) bad = stale(bad, w[k], tag);
            again = retry(bad, it);
        } while (again);
        float s3[3];
#pragma unroll
        for (int k = 0; k < 3; k++) s3[k] = (__uint_as_float(w[4 * k]) + __uint_as_float(w[4 * k + 1])) + (__uint_as_float(w[4 * k + 2]) + __uint_as_float(w[4 * k + 3]));
        const float x = bf_lo(xr), xn = bf_round(bf_round(x - bf_lo(rec.y)) * __uint_as_float(rec.w));
        const bool hi = row & 16;
        const float sg = fmaf(xn, bf_lo(dk), bf_lo(prmt(hi ? y.z : y.x, hi ? y.w : y.y, 0x10 + 0x22 * (row & 1) + 0x44 * ((row >> 3) & 1))));
        const float up = bf_round(bf_round(s3[0] + s3[1] + s3[2]) * bf_hi(rec.x));
        p.out[oi] = __float2bfloat16(fmaf(sg, silu_half(0.5f * bf_round(xn + up)), x));
        if (tile + fi == 0) stg32(p.epoch, tag + 1);
        TS(14);
    }
    }
    LEAVE;
}

typedef CUresult (*EncodeFn)(CUtensorMap*, CUtensorMapDataType, cuuint32_t, void*, const cuuint64_t*, const cuuint64_t*, const cuuint32_t*,
                             const cuuint32_t*, CUtensorMapInterleave, CUtensorMapSwizzle, CUtensorMapL2promotion, CUtensorMapFloatOOBfill);

void make_map(EncodeFn enc, CUtensorMap* m, const void* base, uint64_t cols, uint64_t rows, uint64_t second, uint32_t bc, uint32_t br, CUtensorMapSwizzle sw) {
    cuuint64_t gd[3] = {cols / 2, rows, second ? 2u : 1u};
    cuuint64_t gs[2] = {cols * 2, second ? second : cols * 2 * rows};
    cuuint32_t bd[3] = {bc / 2, br, second ? 2u : 1u}, es[3] = {1, 1, 1};
    enc(m, CU_TENSOR_MAP_DATA_TYPE_UINT32, 3, const_cast<void*>(base), gd, gs, bd, es, CU_TENSOR_MAP_INTERLEAVE_NONE, sw,
        CU_TENSOR_MAP_L2_PROMOTION_L2_128B, CU_TENSOR_MAP_FLOAT_OOB_FILL_NONE);
}

}

extern "C" void kernel_launch(void* const* d_in, const int* in_sizes, int n_in, void* d_out, int out_size) {
    static EncodeFn enc = nullptr;
    static char* gs = nullptr;
    static LaneTab* gt = nullptr;
    static uint32_t* ge = nullptr;
    if (!enc) {
        void* fn = nullptr;
        cudaDriverEntryPointQueryResult qr;
        cudaGetDriverEntryPoint("cuTensorMapEncodeTiled", &fn, cudaEnableDefault, &qr);
        enc = (EncodeFn)fn;
        cudaFuncSetAttribute(fused_kernel, cudaFuncAttributeMaxDynamicSharedMemorySize, SM_TOTAL);
        cudaGetSymbolAddress((void**)&gs, g_s);
        cudaGetSymbolAddress((void**)&ge, g_epoch);
        cudaGetSymbolAddress((void**)&gt, g_tab);
    }
    Hot p;
    Maps m;
    auto in = [&](int i) { return (const __nv_bfloat16*)d_in[i]; };
    p.u = in(0); p.are = in(1); p.aim = in(2); p.bre = in(3); p.bim = in(4); p.cre = in(5); p.cim = in(6);
    p.logdt = in(7); p.dskip = in(8); p.wr = in(10);
    p.out = (__nv_bfloat16*)d_out;
    p.zero = 0;
    p.s = gs;
    p.epoch = ge;
    p.tab = gt;
    const char *wg = (const char*)d_in[11], *wu = (const char*)d_in[12];
    p.swap = wu < wg;
    make_map(enc, &m.u, in(0), D_, L_, 0, ROW / 2, 32, CU_TENSOR_MAP_SWIZZLE_NONE);
    make_map(enc, &m.gu, wu < wg ? wu : wg, F_, D_, wu < wg ? wg - wu : wu - wg, 32, 64, CU_TENSOR_MAP_SWIZZLE_64B);
    make_map(enc, &m.wd, in(13), D_, F_, 64, 32, 64, CU_TENSOR_MAP_SWIZZLE_64B);
    fused_kernel<<<NCTA, NTHREADS, SM_TOTAL>>>(p, m);
}
```
